```python
import torch

def _softmax(x, axis=-1):
    return torch.softmax(x, dim=axis)
def _gelu(x):
    return torch.nn.functional.gelu(x, approximate="tanh")
def _silu(x):
    return torch.nn.functional.silu(x)
def _sigmoid(x):
    return torch.sigmoid(x)
def _layernorm(x, axis=-1, eps=1e-5):
    m = x.mean(dim=axis, keepdim=True)
    v = x.var(dim=axis, keepdim=True, unbiased=False)
    return (x - m) / torch.sqrt(v + eps)
def _scatter_add(tgt, idx, src, axis=0):
    return tgt.clone().index_add_(axis, idx, src)
def _segment_sum(src, seg, n):
    out = torch.zeros((n,) + src.shape[1:], dtype=src.dtype)
    return out.index_add_(0, seg, src)
def _pad(x, pw):
    flat = tuple(v for pair in reversed(pw) for v in pair)
    return torch.nn.functional.pad(x, flat)

kernel_name = 'gated_mix__sliding_local_dilated__dense_activation_squared_relu__prompt'

def setup_inputs():

    _w = (lambda a: (lambda t: t.to(torch.bfloat16) if t.is_floating_point() else t)(torch.as_tensor(a)))
    def _A_setup():
        B, S, D = 1, 2048, 640
        return {
            "x": _w((lambda *s: torch.randn(*s, dtype=torch.bfloat16) * 0.05)(B, S, D)),
            "wqkv": _w((lambda *s: torch.randn(*s, dtype=torch.bfloat16) * 0.8)(D, 3 * D)),
            "wo": _w((lambda *s: torch.randn(*s, dtype=torch.bfloat16) * 0.05)(D, D)),
        }
    _A_in = _A_setup()

    def _B_setup():
        B, S, D, F = 1, 2048, 640, 1728
        return {
            "x": _w((lambda *s: torch.randn(*s, dtype=torch.bfloat16) * 0.05)(B, S, D)),
            "w1": _w((lambda *s: torch.randn(*s, dtype=torch.bfloat16) * 0.2)(D, F)),
            "b1": _w((lambda *s: torch.randn(*s, dtype=torch.bfloat16) * 0.2)(F)),
            "w2": _w((lambda *s: torch.randn(*s, dtype=torch.bfloat16) * 0.2)(F, D)),
            "b2": _w((lambda *s: torch.randn(*s, dtype=torch.bfloat16) * 0.2)(D)),
        }
    _B_in = _B_setup()

    return {
        "A_x": _A_in["x"],
        "A_wqkv": _A_in["wqkv"],
        "A_wo": _A_in["wo"],
        "B_x": _B_in["x"],
        "B_w1": _B_in["w1"],
        "B_b1": _B_in["b1"],
        "B_w2": _B_in["w2"],
        "B_b2": _B_in["b2"],
        "gate_w": _w((lambda *s: torch.randn(*s, dtype=torch.bfloat16) * 0.05)(640) * 16.0),
    }

def reference(A_x, A_wqkv, A_wo, B_x, B_w1, B_b1, B_w2, B_b2, gate_w):
    def _A_ref(x, wqkv, wo):
        B, S, D = x.shape
        H = 32; Dh = D // H
        W, dil = 8, 2
        qkv = (lambda x, *d: x.permute(*d))((x @ wqkv).reshape(B, S, 3, H, Dh), 2, 0, 3, 1, 4)
        q, k, v = qkv[0], qkv[1], qkv[2]
        scale = Dh ** -0.5
        pos = torch.arange(S)
        off = torch.arange(W) * dil
        idx = pos[:, None] - off[None, :]
        mask = idx >= 0
        idx_c = torch.where(mask, idx, 0).reshape(-1)
        kg = k[:, :, idx_c, :].reshape(B, H, S, W, Dh)
        vg = v[:, :, idx_c, :].reshape(B, H, S, W, Dh)
        logits = torch.einsum("bhsd,bhswd->bhsw", q, kg) * scale
        logits = torch.where(mask[None, None, :, :], logits, -1e9)
        attn = _softmax(logits, axis=-1)
        o = torch.einsum("bhsw,bhswd->bhsd", attn, vg)
        return (lambda x, *d: x.permute(*d))(o, 0, 2, 1, 3).reshape(B, S, D) @ wo

    def _B_ref(x, w1, b1, w2, b2):
        h = torch.einsum("bsd,df->bsf", x, w1) + b1
        zero = torch.zeros_like(h)
        r = torch.where(h > zero, h, zero)
        h = r * r
        out = torch.einsum("bsf,fd->bsd", h, w2) + b2
        return out

    x = A_x
    g = _sigmoid((x * gate_w).sum(-1, keepdims=True))
    a = _A_ref(x, A_wqkv, A_wo)
    b = _B_ref(x, B_w1, B_b1, B_w2, B_b2)
    return g * a + (1 - g) * b
```

```cpp
#include <cuda_runtime.h>
#include <cuda_bf16.h>
#include <cuda.h>
#include <stdint.h>

namespace {

constexpr int SEQ = 2048, DM = 640, FF = 1728;
constexpr int ACT_LD = DM + FF;
constexpr int OFF_A = 0;
constexpr int OFF_B = 65536;
constexpr int OFF_STG = 163840;
constexpr int STG_KV = 20480, KC = 1152, KPAR = 20 * KC;
constexpr int STG_BYTES = STG_KV + 2 * KPAR;
constexpr int OFF_BAR = OFF_STG + STG_BYTES;
constexpr int OFF_G = OFF_BAR + 256;
constexpr int OFF_B2 = OFF_G + 512;
constexpr int SMEM_TOTAL = OFF_B2 + 320;
static_assert(SMEM_TOTAL <= 232448, "smem");

#define NPRE 5
#define LAG 4
#define HPACE 400

constexpr int BAR_AF = 0, BAR_AE = 4, BAR_BF = 8, BAR_BE = 11, BAR_CF = 14, BAR_CE = 18, BAR_S1F = 22, BAR_S1E = 23, BAR_S2F = 24,
              BAR_HALO = 25, BAR_OF = 26, BAR_S2E = 27, BAR_X1 = 28, BAR_RQ = 29, BAR_RH = 30, BAR_RO = 31;

constexpr unsigned long long bar_counts() {
  unsigned long long k = 0;
  for (int b = 0; b < 32; b++) {
    const int e = (b >= BAR_AE && b < BAR_BF) ? 1 : ((b >= BAR_BE && b < BAR_CF) || (b >= BAR_CE && b < BAR_S1F)) ? 2
                  : (b == BAR_S1F || b == BAR_S2F || b == BAR_OF) ? 3 : 0;
    k |= (unsigned long long)e << (2 * b);
  }
  return k;
}
constexpr unsigned long long BAR_COUNTS = bar_counts();

constexpr int FL_H = 0, FL_O = 1;

struct Maps {
  CUtensorMap ax[2];
  CUtensorMap w1f, w1n[2];
  CUtensorMap rsrc, rdst;
  CUtensorMap wq;
  CUtensorMap hs, hn[2];
  CUtensorMap os;
  CUtensorMap hf;
  CUtensorMap w2f, w2n, wof, won;
  CUtensorMap of, on;
};
constexpr int NMAPS = sizeof(Maps) / sizeof(CUtensorMap);

__device__ __nv_bfloat16 g_act[SEQ * ACT_LD];
__device__ __nv_bfloat16 g_wqkv[8 * DM * 256];
__device__ uint4 g_halo[16 * 8 * 320];
__device__ uint4 g_part[128 * 10 * 128];
__device__ unsigned g_flags[16 * 32];
__device__ unsigned g_rep[8 * 32];
__device__ unsigned g_done[32];
#define PROF3(slot) do { } while (0)
#define PROF2(slot) do { } while (0)
#define PROF(slot) do { } while (0)

__device__ __forceinline__ long long gtime() { long long t; asm volatile("mov.u64 %0, %%globaltimer;" : "=l"(t)); return t; }
__device__ __forceinline__ uint32_t smem_u32(const void* p) { return (uint32_t)__cvta_generic_to_shared(p); }
__device__ __forceinline__ void mbar_init(uint32_t bar, uint32_t cnt) { asm volatile("mbarrier.init.shared::cta.b64 [%0], %1;" ::"r"(bar), "r"(cnt) : "memory"); }
__device__ __forceinline__ void mbar_expect_tx(uint32_t bar, uint32_t bytes) { asm volatile("mbarrier.arrive.expect_tx.shared::cta.b64 _, [%0], %1;" ::"r"(bar), "r"(bytes) : "memory"); }
__device__ __forceinline__ void mbar_wait(uint32_t bar, uint32_t parity) {
  asm volatile(
      "{\n.reg .pred p;\n.reg .u32 c;\nmov.u32 c, 0;\n"
      "LAB_WAIT:\n"
      "mbarrier.try_wait.parity.shared::cta.b64 p, [%0], %1;\n"
      "@p bra DONE;\n"
      "add.u32 c, c, 1;\n"
      "setp.lt.u32 p, c, 0x4000000;\n"
      "@p bra LAB_WAIT;\n"
      "trap;\n"
      "DONE:\n}" ::"r"(bar), "r"(parity) : "memory");
}
__device__ __forceinline__ void mbar_arrive(uint32_t bar) { asm volatile("mbarrier.arrive.shared::cta.b64 _, [%0];" ::"r"(bar) : "memory"); }
__device__ __forceinline__ void mbar_arrive_cluster(uint32_t bar, uint32_t cta) {
  asm volatile("{\n.reg .b32 ra;\nmapa.shared::cluster.u32 ra, %0, %1;\nmbarrier.arrive.shared::cluster.b64 _, [ra];\n}" ::"r"(bar), "r"(cta) : "memory");
}
__device__ __forceinline__ void tma2d(uint32_t dst, const CUtensorMap* tm, uint32_t bar, int c0, int c1) {
  asm volatile("cp.async.bulk.tensor.2d.shared::cluster.global.mbarrier::complete_tx::bytes [%0], [%1, {%3, %4}], [%2];"
               ::"r"(dst), "l"(tm), "r"(bar), "r"(c0), "r"(c1) : "memory");
}
__device__ __forceinline__ void tma3d(uint32_t dst, const CUtensorMap* tm, uint32_t bar, int c0, int c1) {
  asm volatile("cp.async.bulk.tensor.3d.shared::cluster.global.mbarrier::complete_tx::bytes [%0], [%1, {%3, %4, %5}], [%2];"
               ::"r"(dst), "l"(tm), "r"(bar), "r"(c0), "r"(c1), "r"(0) : "memory");
}
__device__ __forceinline__ void tma2d_mc(uint32_t dst, const CUtensorMap* tm, uint32_t bar, int c0, int c1) {
  asm volatile("cp.async.bulk.tensor.2d.shared::cluster.global.mbarrier::complete_tx::bytes.multicast::cluster [%0], [%1, {%3, %4}], [%2], %5;"
               ::"r"(dst), "l"(tm), "r"(bar), "r"(c0), "r"(c1), "h"((uint16_t)3) : "memory");
}
__device__ __forceinline__ void tma2d_store(const CUtensorMap* tm, uint32_t src, int c0, int c1) {
  asm volatile("cp.async.bulk.tensor.2d.global.shared::cta.bulk_group [%0, {%2, %3}], [%1];" ::"l"(tm), "r"(src), "r"(c0), "r"(c1) : "memory");
}
__device__ __forceinline__ void tma3d_store(const CUtensorMap* tm, uint32_t src, int c0, int c1) {
  asm volatile("cp.async.bulk.tensor.3d.global.shared::cta.bulk_group [%0, {%2, %3, %4}], [%1];" ::"l"(tm), "r"(src), "r"(c0), "r"(c1), "r"(0) : "memory");
}
__device__ __forceinline__ void pf2d(const CUtensorMap* tm, int c0, int c1) {
  asm volatile("cp.async.bulk.prefetch.tensor.2d.L2.global [%0, {%1, %2}];" ::"l"(tm), "r"(c0), "r"(c1) : "memory");
}
__device__ __forceinline__ void pf3d(const CUtensorMap* tm, int c0, int c1) {
  asm volatile("cp.async.bulk.prefetch.tensor.3d.L2.global [%0, {%1, %2, %3}];" ::"l"(tm), "r"(c0), "r"(c1), "r"(0) : "memory");
}
__device__ __forceinline__ void bulk_commit() { asm volatile("cp.async.bulk.commit_group;" ::: "memory"); }
__device__ __forceinline__ void bulk_wait_read() { asm volatile("cp.async.bulk.wait_group.read 0;" ::: "memory"); }
__device__ __forceinline__ void bulk_wait() { asm volatile("cp.async.bulk.wait_group 0;" ::: "memory"); }
__device__ __forceinline__ void prefetch_tm(const CUtensorMap* tm) { asm volatile("prefetch.tensormap [%0];" ::"l"(tm) : "memory"); }
__device__ __forceinline__ void prefetch_l2(const void* p, uint32_t bytes) { asm volatile("cp.async.bulk.prefetch.L2.global [%0], %1;" ::"l"(p), "r"(bytes) : "memory"); }
__device__ __forceinline__ unsigned ld_relaxed(const unsigned* p) { unsigned v; asm volatile("ld.relaxed.gpu.global.u32 %0, [%1];" : "=r"(v) : "l"(p) : "memory"); return v; }
__device__ __forceinline__ uint4 ld_relaxed4(const uint4* p) {
  uint4 v; asm volatile("ld.relaxed.gpu.global.v4.u32 {%0,%1,%2,%3}, [%4];" : "=r"(v.x), "=r"(v.y), "=r"(v.z), "=r"(v.w) : "l"(p) : "memory"); return v;
}
__device__ __forceinline__ void st_relaxed4(uint4* p, uint4 v) {
  asm volatile("st.relaxed.gpu.global.v4.u32 [%0], {%1,%2,%3,%4};" ::"l"(p), "r"(v.x), "r"(v.y), "r"(v.z), "r"(v.w) : "memory");
}
__device__ __forceinline__ void red_release(unsigned* p, unsigned v) { asm volatile("red.release.gpu.global.add.u32 [%0], %1;" ::"l"(p), "r"(v) : "memory"); }
__device__ __forceinline__ void wait_flag(const unsigned* p, unsigned target) {
  asm volatile(
      "{\n.reg .pred p;\n.reg .u32 c, v;\nmov.u32 c, 0;\n"
      "LAB_WAIT:\n"
      "ld.acquire.gpu.global.u32 v, [%0];\n"
      "sub.u32 v, v, %1;\n"
      "setp.ge.s32 p, v, 0;\n"
      "@p bra DONE;\n"
      "add.u32 c, c, 1;\n"
      "setp.lt.u32 p, c, 0x2000000;\n"
      "@p bra LAB_WAIT;\n"
      "trap;\n"
      "DONE:\n}" ::"l"(p), "r"(target) : "memory");
}
__device__ __forceinline__ int opaque(int x) { asm volatile("" : "+r"(x)); return x; }
__device__ __forceinline__ void bar_sync(int id, int n) { asm volatile("bar.sync %0, %1;" ::"r"(id), "r"(n) : "memory"); }
__device__ __forceinline__ void bar_arrive(int id, int n) { asm volatile("bar.arrive %0, %1;" ::"r"(id), "r"(n) : "memory"); }
__device__ __forceinline__ void fence_async() { asm volatile("fence.proxy.async.global;" ::: "memory"); }
__device__ __forceinline__ void fence_async_smem() { asm volatile("fence.proxy.async.shared::cta;" ::: "memory"); }
__device__ __forceinline__ void cluster_arrive() { asm volatile("barrier.cluster.arrive.relaxed.aligned;" ::: "memory"); }
__device__ __forceinline__ void cluster_wait() { asm volatile("barrier.cluster.wait.aligned;" ::: "memory"); }
__device__ __forceinline__ uint64_t mkdesc(uint32_t addr, uint32_t lbo, uint32_t sbo) {
  return (uint64_t)((addr & 0x3FFFF) >> 4) | ((uint64_t)(lbo >> 4) << 16) | ((uint64_t)(sbo >> 4) << 32) | (1ull << 62);
}
__device__ __forceinline__ uint32_t pack_bf16(float lo, float hi) { uint32_t r; asm("cvt.rn.bf16x2.f32 %0, %1, %2;" : "=r"(r) : "f"(hi), "f"(lo)); return r; }
__device__ __forceinline__ uint32_t pack_bf16_relu(float lo, float hi) { uint32_t r; asm("cvt.rn.relu.bf16x2.f32 %0, %1, %2;" : "=r"(r) : "f"(hi), "f"(lo)); return r; }
__device__ __forceinline__ uint32_t mul_bf16x2(uint32_t a, uint32_t b) { uint32_t r; asm("mul.rn.bf16x2 %0, %1, %2;" : "=r"(r) : "r"(a), "r"(b)); return r; }
__device__ __forceinline__ float bf_lo(uint32_t v) { return __uint_as_float(v << 16); }
__device__ __forceinline__ float bf_hi(uint32_t v) { return __uint_as_float(v & 0xffff0000u); }
__device__ __forceinline__ void stsm_x4(uint32_t a, uint32_t r0, uint32_t r1, uint32_t r2, uint32_t r3) {
  asm volatile("stmatrix.sync.aligned.m8n8.x4.shared.b16 [%0], {%1, %2, %3, %4};" ::"r"(a), "r"(r0), "r"(r1), "r"(r2), "r"(r3) : "memory");
}
__device__ __forceinline__ void ldsm_x4(uint32_t a, uint32_t (&r)[4]) {
  asm volatile("ldmatrix.sync.aligned.m8n8.x4.shared.b16 {%0, %1, %2, %3}, [%4];" : "=r"(r[0]), "=r"(r[1]), "=r"(r[2]), "=r"(r[3]) : "r"(a) : "memory");
}
__device__ __forceinline__ void ldsm_x4_t(uint32_t a, uint32_t (&r)[4]) {
  asm volatile("ldmatrix.sync.aligned.m8n8.x4.trans.shared.b16 {%0, %1, %2, %3}, [%4];" : "=r"(r[0]), "=r"(r[1]), "=r"(r[2]), "=r"(r[3]) : "r"(a) : "memory");
}
__device__ __forceinline__ void mma16(float (&d)[4], uint32_t a0, uint32_t a1, uint32_t a2, uint32_t a3, uint32_t b0, uint32_t b1) {
  asm volatile("mma.sync.aligned.m16n8k16.row.col.f32.bf16.bf16.f32 {%0,%1,%2,%3}, {%4,%5,%6,%7}, {%8,%9}, {%0,%1,%2,%3};"
               : "+f"(d[0]), "+f"(d[1]), "+f"(d[2]), "+f"(d[3]) : "r"(a0), "r"(a1), "r"(a2), "r"(a3), "r"(b0), "r"(b1));
}
__device__ __forceinline__ void mma8(float (&d)[4], uint32_t a0, uint32_t a1, uint32_t b0) {
  asm volatile("mma.sync.aligned.m16n8k8.row.col.f32.bf16.bf16.f32 {%0,%1,%2,%3}, {%4,%5}, {%6}, {%0,%1,%2,%3};"
               : "+f"(d[0]), "+f"(d[1]), "+f"(d[2]), "+f"(d[3]) : "r"(a0), "r"(a1), "r"(b0));
}
__device__ __forceinline__ uint4 lds128(uint32_t a) { uint4 v; asm volatile("ld.shared.v4.u32 {%0,%1,%2,%3}, [%4];" : "=r"(v.x), "=r"(v.y), "=r"(v.z), "=r"(v.w) : "r"(a) : "memory"); return v; }
__device__ __forceinline__ void sts128(uint32_t a, uint4 v) { asm volatile("st.shared.v4.u32 [%0], {%1,%2,%3,%4};" ::"r"(a), "r"(v.x), "r"(v.y), "r"(v.z), "r"(v.w) : "memory"); }
__device__ __forceinline__ void sts32(uint32_t a, uint32_t v) { asm volatile("st.shared.u32 [%0], %1;" ::"r"(a), "r"(v) : "memory"); }
__device__ __forceinline__ void sts32f(uint32_t a, float v) { asm volatile("st.shared.f32 [%0], %1;" ::"r"(a), "f"(v) : "memory"); }
__device__ __forceinline__ uint32_t lds32(uint32_t a) { uint32_t v; asm volatile("ld.shared.u32 %0, [%1];" : "=r"(v) : "r"(a) : "memory"); return v; }
__device__ __forceinline__ float lds32f(uint32_t a) { float v; asm volatile("ld.shared.f32 %0, [%1];" : "=f"(v) : "r"(a) : "memory"); return v; }
__device__ __forceinline__ float ex2(float x) { float r; asm("ex2.approx.ftz.f32 %0, %1;" : "=f"(r) : "f"(x)); return r; }
__device__ __forceinline__ float rcp(float x) { float r; asm("rcp.approx.ftz.f32 %0, %1;" : "=f"(r) : "f"(x)); return r; }

template <int M> __device__ __forceinline__ void wgmma_n160(float (&d)[M], uint64_t da, uint64_t db, int scale_d) {
  asm volatile("{\n.reg .pred p;\nsetp.ne.b32 p, %82, 0;\n"
    "wgmma.mma_async.sync.aligned.m64n160k16.f32.bf16.bf16 "
    "{%0, %1, %2, %3, %4, %5, %6, %7, %8, %9, %10, %11, %12, %13, %14, %15, "
    "%16, %17, %18, %19, %20, %21, %22, %23, %24, %25, %26, %27, %28, %29, %30, %31, "
    "%32, %33, %34, %35, %36, %37, %38, %39, %40, %41, %42, %43, %44, %45, %46, %47, "
    "%48, %49, %50, %51, %52, %53, %54, %55, %56, %57, %58, %59, %60, %61, %62, %63, "
    "%64, %65, %66, %67, %68, %69, %70, %71, %72, %73, %74, %75, %76, %77, %78, %79}, "
    "%80, %81, p, 1, 1, 0, 1;\n}\n"
    : "+f"(d[0]), "+f"(d[1]), "+f"(d[2]), "+f"(d[3]), "+f"(d[4]), "+f"(d[5]), "+f"(d[6]), "+f"(d[7]),
      "+f"(d[8]), "+f"(d[9]), "+f"(d[10]), "+f"(d[11]), "+f"(d[12]), "+f"(d[13]), "+f"(d[14]), "+f"(d[15]),
      "+f"(d[16]), "+f"(d[17]), "+f"(d[18]), "+f"(d[19]), "+f"(d[20]), "+f"(d[21]), "+f"(d[22]), "+f"(d[23]),
      "+f"(d[24]), "+f"(d[25]), "+f"(d[26]), "+f"(d[27]), "+f"(d[28]), "+f"(d[29]), "+f"(d[30]), "+f"(d[31]),
      "+f"(d[32]), "+f"(d[33]), "+f"(d[34]), "+f"(d[35]), "+f"(d[36]), "+f"(d[37]), "+f"(d[38]), "+f"(d[39]),
      "+f"(d[40]), "+f"(d[41]), "+f"(d[42]), "+f"(d[43]), "+f"(d[44]), "+f"(d[45]), "+f"(d[46]), "+f"(d[47]),
      "+f"(d[48]), "+f"(d[49]), "+f"(d[50]), "+f"(d[51]), "+f"(d[52]), "+f"(d[53]), "+f"(d[54]), "+f"(d[55]),
      "+f"(d[56]), "+f"(d[57]), "+f"(d[58]), "+f"(d[59]), "+f"(d[60]), "+f"(d[61]), "+f"(d[62]), "+f"(d[63]),
      "+f"(d[64]), "+f"(d[65]), "+f"(d[66]), "+f"(d[67]), "+f"(d[68]), "+f"(d[69]), "+f"(d[70]), "+f"(d[71]),
      "+f"(d[72]), "+f"(d[73]), "+f"(d[74]), "+f"(d[75]), "+f"(d[76]), "+f"(d[77]), "+f"(d[78]), "+f"(d[79])
    : "l"(da), "l"(db), "r"(scale_d));
}
template <int M> __device__ __forceinline__ void wgmma_n208(float (&d)[M], uint64_t da, uint64_t db, int scale_d) {
  asm volatile("{\n.reg .pred p;\nsetp.ne.b32 p, %106, 0;\n"
    "wgmma.mma_async.sync.aligned.m64n208k16.f32.bf16.bf16 "
    "{%0, %1, %2, %3, %4, %5, %6, %7, %8, %9, %10, %11, %12, %13, %14, %15, "
    "%16, %17, %18, %19, %20, %21, %22, %23, %24, %25, %26, %27, %28, %29, %30, %31, "
    "%32, %33, %34, %35, %36, %37, %38, %39, %40, %41, %42, %43, %44, %45, %46, %47, "
    "%48, %49, %50, %51, %52, %53, %54, %55, %56, %57, %58, %59, %60, %61, %62, %63, "
    "%64, %65, %66, %67, %68, %69, %70, %71, %72, %73, %74, %75, %76, %77, %78, %79, "
    "%80, %81, %82, %83, %84, %85, %86, %87, %88, %89, %90, %91, %92, %93, %94, %95, "
    "%96, %97, %98, %99, %100, %101, %102, %103}, "
    "%104, %105, p, 1, 1, 0, 1;\n}\n"
    : "+f"(d[0]), "+f"(d[1]), "+f"(d[2]), "+f"(d[3]), "+f"(d[4]), "+f"(d[5]), "+f"(d[6]), "+f"(d[7]),
      "+f"(d[8]), "+f"(d[9]), "+f"(d[10]), "+f"(d[11]), "+f"(d[12]), "+f"(d[13]), "+f"(d[14]), "+f"(d[15]),
      "+f"(d[16]), "+f"(d[17]), "+f"(d[18]), "+f"(d[19]), "+f"(d[20]), "+f"(d[21]), "+f"(d[22]), "+f"(d[23]),
      "+f"(d[24]), "+f"(d[25]), "+f"(d[26]), "+f"(d[27]), "+f"(d[28]), "+f"(d[29]), "+f"(d[30]), "+f"(d[31]),
      "+f"(d[32]), "+f"(d[33]), "+f"(d[34]), "+f"(d[35]), "+f"(d[36]), "+f"(d[37]), "+f"(d[38]), "+f"(d[39]),
      "+f"(d[40]), "+f"(d[41]), "+f"(d[42]), "+f"(d[43]), "+f"(d[44]), "+f"(d[45]), "+f"(d[46]), "+f"(d[47]),
      "+f"(d[48]), "+f"(d[49]), "+f"(d[50]), "+f"(d[51]), "+f"(d[52]), "+f"(d[53]), "+f"(d[54]), "+f"(d[55]),
      "+f"(d[56]), "+f"(d[57]), "+f"(d[58]), "+f"(d[59]), "+f"(d[60]), "+f"(d[61]), "+f"(d[62]), "+f"(d[63]),
      "+f"(d[64]), "+f"(d[65]), "+f"(d[66]), "+f"(d[67]), "+f"(d[68]), "+f"(d[69]), "+f"(d[70]), "+f"(d[71]),
      "+f"(d[72]), "+f"(d[73]), "+f"(d[74]), "+f"(d[75]), "+f"(d[76]), "+f"(d[77]), "+f"(d[78]), "+f"(d[79]),
      "+f"(d[80]), "+f"(d[81]), "+f"(d[82]), "+f"(d[83]), "+f"(d[84]), "+f"(d[85]), "+f"(d[86]), "+f"(d[87]),
      "+f"(d[88]), "+f"(d[89]), "+f"(d[90]), "+f"(d[91]), "+f"(d[92]), "+f"(d[93]), "+f"(d[94]), "+f"(d[95]),
      "+f"(d[96]), "+f"(d[97]), "+f"(d[98]), "+f"(d[99]), "+f"(d[100]), "+f"(d[101]), "+f"(d[102]), "+f"(d[103])
    : "l"(da), "l"(db), "r"(scale_d));
}
template <int M> __device__ __forceinline__ void wgmma_n224(float (&d)[M], uint64_t da, uint64_t db, int scale_d) {
  asm volatile("{\n.reg .pred p;\nsetp.ne.b32 p, %114, 0;\n"
    "wgmma.mma_async.sync.aligned.m64n224k16.f32.bf16.bf16 "
    "{%0, %1, %2, %3, %4, %5, %6, %7, %8, %9, %10, %11, %12, %13, %14, %15, "
    "%16, %17, %18, %19, %20, %21, %22, %23, %24, %25, %26, %27, %28, %29, %30, %31, "
    "%32, %33, %34, %35, %36, %37, %38, %39, %40, %41, %42, %43, %44, %45, %46, %47, "
    "%48, %49, %50, %51, %52, %53, %54, %55, %56, %57, %58, %59, %60, %61, %62, %63, "
    "%64, %65, %66, %67, %68, %69, %70, %71, %72, %73, %74, %75, %76, %77, %78, %79, "
    "%80, %81, %82, %83, %84, %85, %86, %87, %88, %89, %90, %91, %92, %93, %94, %95, "
    "%96, %97, %98, %99, %100, %101, %102, %103, %104, %105, %106, %107, %108, %109, %110, %111}, "
    "%112, %113, p, 1, 1, 0, 1;\n}\n"
    : "+f"(d[0]), "+f"(d[1]), "+f"(d[2]), "+f"(d[3]), "+f"(d[4]), "+f"(d[5]), "+f"(d[6]), "+f"(d[7]),
      "+f"(d[8]), "+f"(d[9]), "+f"(d[10]), "+f"(d[11]), "+f"(d[12]), "+f"(d[13]), "+f"(d[14]), "+f"(d[15]),
      "+f"(d[16]), "+f"(d[17]), "+f"(d[18]), "+f"(d[19]), "+f"(d[20]), "+f"(d[21]), "+f"(d[22]), "+f"(d[23]),
      "+f"(d[24]), "+f"(d[25]), "+f"(d[26]), "+f"(d[27]), "+f"(d[28]), "+f"(d[29]), "+f"(d[30]), "+f"(d[31]),
      "+f"(d[32]), "+f"(d[33]), "+f"(d[34]), "+f"(d[35]), "+f"(d[36]), "+f"(d[37]), "+f"(d[38]), "+f"(d[39]),
      "+f"(d[40]), "+f"(d[41]), "+f"(d[42]), "+f"(d[43]), "+f"(d[44]), "+f"(d[45]), "+f"(d[46]), "+f"(d[47]),
      "+f"(d[48]), "+f"(d[49]), "+f"(d[50]), "+f"(d[51]), "+f"(d[52]), "+f"(d[53]), "+f"(d[54]), "+f"(d[55]),
      "+f"(d[56]), "+f"(d[57]), "+f"(d[58]), "+f"(d[59]), "+f"(d[60]), "+f"(d[61]), "+f"(d[62]), "+f"(d[63]),
      "+f"(d[64]), "+f"(d[65]), "+f"(d[66]), "+f"(d[67]), "+f"(d[68]), "+f"(d[69]), "+f"(d[70]), "+f"(d[71]),
      "+f"(d[72]), "+f"(d[73]), "+f"(d[74]), "+f"(d[75]), "+f"(d[76]), "+f"(d[77]), "+f"(d[78]), "+f"(d[79]),
      "+f"(d[80]), "+f"(d[81]), "+f"(d[82]), "+f"(d[83]), "+f"(d[84]), "+f"(d[85]), "+f"(d[86]), "+f"(d[87]),
      "+f"(d[88]), "+f"(d[89]), "+f"(d[90]), "+f"(d[91]), "+f"(d[92]), "+f"(d[93]), "+f"(d[94]), "+f"(d[95]),
      "+f"(d[96]), "+f"(d[97]), "+f"(d[98]), "+f"(d[99]), "+f"(d[100]), "+f"(d[101]), "+f"(d[102]), "+f"(d[103]),
      "+f"(d[104]), "+f"(d[105]), "+f"(d[106]), "+f"(d[107]), "+f"(d[108]), "+f"(d[109]), "+f"(d[110]), "+f"(d[111])
    : "l"(da), "l"(db), "r"(scale_d));
}
template <int M> __device__ __forceinline__ void wgmma_n248(float (&d)[M], uint64_t da, uint64_t db, int scale_d) {
  asm volatile("{\n.reg .pred p;\nsetp.ne.b32 p, %126, 0;\n"
    "wgmma.mma_async.sync.aligned.m64n248k16.f32.bf16.bf16 "
    "{%0, %1, %2, %3, %4, %5, %6, %7, %8, %9, %10, %11, %12, %13, %14, %15, "
    "%16, %17, %18, %19, %20, %21, %22, %23, %24, %25, %26, %27, %28, %29, %30, %31, "
    "%32, %33, %34, %35, %36, %37, %38, %39, %40, %41, %42, %43, %44, %45, %46, %47, "
    "%48, %49, %50, %51, %52, %53, %54, %55, %56, %57, %58, %59, %60, %61, %62, %63, "
    "%64, %65, %66, %67, %68, %69, %70, %71, %72, %73, %74, %75, %76, %77, %78, %79, "
    "%80, %81, %82, %83, %84, %85, %86, %87, %88, %89, %90, %91, %92, %93, %94, %95, "
    "%96, %97, %98, %99, %100, %101, %102, %103, %104, %105, %106, %107, %108, %109, %110, %111, "
    "%112, %113, %114, %115, %116, %117, %118, %119, %120, %121, %122, %123}, "
    "%124, %125, p, 1, 1, 0, 1;\n}\n"
    : "+f"(d[0]), "+f"(d[1]), "+f"(d[2]), "+f"(d[3]), "+f"(d[4]), "+f"(d[5]), "+f"(d[6]), "+f"(d[7]),
      "+f"(d[8]), "+f"(d[9]), "+f"(d[10]), "+f"(d[11]), "+f"(d[12]), "+f"(d[13]), "+f"(d[14]), "+f"(d[15]),
      "+f"(d[16]), "+f"(d[17]), "+f"(d[18]), "+f"(d[19]), "+f"(d[20]), "+f"(d[21]), "+f"(d[22]), "+f"(d[23]),
      "+f"(d[24]), "+f"(d[25]), "+f"(d[26]), "+f"(d[27]), "+f"(d[28]), "+f"(d[29]), "+f"(d[30]), "+f"(d[31]),
      "+f"(d[32]), "+f"(d[33]), "+f"(d[34]), "+f"(d[35]), "+f"(d[36]), "+f"(d[37]), "+f"(d[38]), "+f"(d[39]),
      "+f"(d[40]), "+f"(d[41]), "+f"(d[42]), "+f"(d[43]), "+f"(d[44]), "+f"(d[45]), "+f"(d[46]), "+f"(d[47]),
      "+f"(d[48]), "+f"(d[49]), "+f"(d[50]), "+f"(d[51]), "+f"(d[52]), "+f"(d[53]), "+f"(d[54]), "+f"(d[55]),
      "+f"(d[56]), "+f"(d[57]), "+f"(d[58]), "+f"(d[59]), "+f"(d[60]), "+f"(d[61]), "+f"(d[62]), "+f"(d[63]),
      "+f"(d[64]), "+f"(d[65]), "+f"(d[66]), "+f"(d[67]), "+f"(d[68]), "+f"(d[69]), "+f"(d[70]), "+f"(d[71]),
      "+f"(d[72]), "+f"(d[73]), "+f"(d[74]), "+f"(d[75]), "+f"(d[76]), "+f"(d[77]), "+f"(d[78]), "+f"(d[79]),
      "+f"(d[80]), "+f"(d[81]), "+f"(d[82]), "+f"(d[83]), "+f"(d[84]), "+f"(d[85]), "+f"(d[86]), "+f"(d[87]),
      "+f"(d[88]), "+f"(d[89]), "+f"(d[90]), "+f"(d[91]), "+f"(d[92]), "+f"(d[93]), "+f"(d[94]), "+f"(d[95]),
      "+f"(d[96]), "+f"(d[97]), "+f"(d[98]), "+f"(d[99]), "+f"(d[100]), "+f"(d[101]), "+f"(d[102]), "+f"(d[103]),
      "+f"(d[104]), "+f"(d[105]), "+f"(d[106]), "+f"(d[107]), "+f"(d[108]), "+f"(d[109]), "+f"(d[110]), "+f"(d[111]),
      "+f"(d[112]), "+f"(d[113]), "+f"(d[114]), "+f"(d[115]), "+f"(d[116]), "+f"(d[117]), "+f"(d[118]), "+f"(d[119]),
      "+f"(d[120]), "+f"(d[121]), "+f"(d[122]), "+f"(d[123])
    : "l"(da), "l"(db), "r"(scale_d));
}

template <int N> __device__ __forceinline__ void reg_fence(float (&d)[N]) {
#pragma unroll
  for (int x = 0; x < N; x++) asm volatile("" : "+f"(d[x])::"memory");
}
template <int N, int M> __device__ __forceinline__ void wg_mma(float (&d)[M], uint64_t da, uint64_t db, int sc) {
  if constexpr (N == 160) wgmma_n160(d, da, db, sc);
  else if constexpr (N == 208) wgmma_n208(d, da, db, sc);
  else if constexpr (N == 224) wgmma_n224(d, da, db, sc);
  else wgmma_n248(d, da, db, sc);
}

struct Pipe { uint32_t na, sb, pb; };

template <int N, int M, bool OUTP, bool ZERO>
__device__ __forceinline__ void mainloop(float (&acc)[M], int nblk, Pipe& p, uint32_t sbase, int wg, bool elect, int norel, int hold) {
  const uint32_t bars = sbase + OFF_BAR;
  constexpr uint32_t BSLOT = OUTP ? 24576 : 32768;
  constexpr int FULL = OUTP ? BAR_CF : BAR_BF, EMPTY = OUTP ? BAR_CE : BAR_BE;
  const uint64_t dA0 = mkdesc(sbase + OFF_A + wg * 8192, 16, 1024);
  const uint64_t dB0 = mkdesc(sbase + OFF_B, 8192, 1024);
  uint32_t prevA = 0, prevB = 0;
  if (!ZERO) reg_fence(acc);
#pragma unroll 1
  for (int kb = 0; kb < nblk; ++kb) {
    if (kb == hold) {
      asm volatile("wgmma.wait_group.sync.aligned 0;" ::: "memory");
      if (elect && prevA) { mbar_arrive(prevA); mbar_arrive_cluster(prevB, 0); mbar_arrive_cluster(prevB, 1); }
      prevA = 0;
      bar_sync(3, 256);
    }
    const uint32_t sa = p.na & 3;
    mbar_wait(bars + (BAR_AF + sa) * 8, (p.na >> 2) & 1);
    mbar_wait(bars + (FULL + p.sb) * 8, p.pb);
    if (elect && wg == 0) PROF2(p.na);
    if (elect && wg == 1) PROF3(p.na);
    const uint64_t da = dA0 + (uint64_t)(sa * 1024);
    const uint64_t db = dB0 + (uint64_t)(p.sb * (BSLOT >> 4));
    reg_fence(acc);
    asm volatile("wgmma.fence.sync.aligned;" ::: "memory");
    wg_mma<N>(acc, da, db, ZERO ? (kb > 0) : 1);
    asm volatile("wgmma.commit_group.sync.aligned;" ::: "memory");
    asm volatile("wgmma.wait_group.sync.aligned 1;" ::: "memory");
    if (elect && wg == 0) PROF3(64 + p.na);
    if (elect && prevA) { mbar_arrive(prevA); mbar_arrive_cluster(prevB, 0); mbar_arrive_cluster(prevB, 1); }
    wg_mma<N>(acc, da + 2, db + 128, 1);
    wg_mma<N>(acc, da + 4, db + 256, 1);
    wg_mma<N>(acc, da + 6, db + 384, 1);
    asm volatile("wgmma.commit_group.sync.aligned;" ::: "memory");
    prevA = (kb < nblk - norel) ? bars + (BAR_AE + sa) * 8 : 0;
    prevB = bars + (EMPTY + p.sb) * 8;
    ++p.na;
    if (OUTP) {
      p.sb = (p.sb + 1) & 3;
      if (p.sb == 3) p.pb ^= 1;
    } else {
      if (++p.sb == 3) { p.sb = 0; p.pb ^= 1; }
    }
  }
  asm volatile("wgmma.wait_group.sync.aligned 0;" ::: "memory");
  reg_fence(acc);
  if (elect && prevA) { mbar_arrive(prevA); mbar_arrive_cluster(prevB, 0); mbar_arrive_cluster(prevB, 1); }
}

struct Role {
  int i, c, s, rank;
  int full0, part0;
};

__device__ __forceinline__ void softmax4(const float (&s0)[4], const float (&s1)[4], const float (&s2)[4], bool p0, bool p1, uint32_t msk,
                                         uint32_t& pa0, uint32_t& pa2, uint32_t& pa3, uint32_t& pb1) {
  constexpr float SC = 0.22360679774997896f * 1.4426950408889634f;
  const float l0 = p0 ? s1[0] : s0[0], l1 = p1 ? s1[1] : s0[1], h0 = p0 ? s2[2] : s1[2], h1 = p1 ? s2[3] : s1[3];
  float ml = fmaxf(l0, l1), mh = fmaxf(h0, h1);
  ml = fmaxf(ml, __shfl_xor_sync(0xffffffffu, ml, 1)); mh = fmaxf(mh, __shfl_xor_sync(0xffffffffu, mh, 1));
  ml = fmaxf(ml, __shfl_xor_sync(0xffffffffu, ml, 2)); mh = fmaxf(mh, __shfl_xor_sync(0xffffffffu, mh, 2));
  ml *= SC; mh *= SC;
  const uint32_t pl = pack_bf16(ex2(fmaf(l0, SC, -ml)), ex2(fmaf(l1, SC, -ml)));
  const uint32_t ph = pack_bf16(ex2(fmaf(h0, SC, -mh)), ex2(fmaf(h1, SC, -mh)));
  pa0 = pl & ~msk; pa2 = pl & msk; pa3 = ph & ~msk; pb1 = ph & msk;
}

__device__ __forceinline__ void attention(uint32_t stg, uint32_t gsm, int wg, int warp, int lane, bool first) {
  const int t = lane & 3, g = lane >> 2;
  const uint32_t qb = stg + (wg * 4 + warp) * 2560;
  const uint32_t kb = stg + STG_KV + wg * KPAR + warp * 256 + min(lane >> 3, 2) * 128 + (lane & 7) * 16;
  const bool p0 = 2 * t <= g, p1 = 2 * t + 1 <= g;
  const uint32_t msk = (p0 ? 0xffffu : 0u) | (p1 ? 0xffff0000u : 0u);
  const uint32_t mA = t < 2 ? 0xffffffffu : 0u;
  const float ninf = first ? -INFINITY : 0.f;
  const float ezl = lds32f(gsm + (2 * (warp * 16 + g) + wg) * 4), ezh = lds32f(gsm + (2 * (warp * 16 + g + 8) + wg) * 4);
  uint32_t q[5][4];
#pragma unroll
  for (int c = 0; c < 5; c++) ldsm_x4(qb + c * 512 + lane * 16, q[c]);
  __syncwarp();
  const uint32_t ob = qb + (lane & 15) * 160 + (lane >> 4) * 16;
  uint32_t ores[2][10];
#pragma unroll
  for (int hp = 0; hp < 2; hp++) {
#define QF(x, half) q[(5 * hp + (x)) >> 1][(((5 * hp + (x)) & 1) << 1) + (half)]
    uint32_t kf[5][4];
#pragma unroll
    for (int c = 0; c < 5; c++) ldsm_x4(kb + (5 * hp + c) * KC, kf[c]);
    float sa[3][4], sb[3][4];
#pragma unroll
    for (int j = 0; j < 3; j++) {
      sa[j][0] = sa[j][1] = sb[j][0] = sb[j][1] = (j == 0) ? ninf : 0.f;
      sa[j][2] = sa[j][3] = sb[j][2] = sb[j][3] = 0.f;
      mma16(sa[j], QF(0, 0), QF(0, 1), QF(1, 0), QF(1, 1), kf[0][j], kf[1][j]);
      mma16(sb[j], QF(3, 0), QF(3, 1), QF(4, 0), QF(4, 1), kf[3][j], kf[4][j]);
      mma8(sa[j], QF(2, 0) & mA, QF(2, 1) & mA, kf[2][j]);
      mma8(sb[j], QF(2, 0) & ~mA, QF(2, 1) & ~mA, kf[2][j]);
    }
    uint32_t vf[5][4];
#pragma unroll
    for (int c = 0; c < 5; c++) ldsm_x4_t(kb + (10 + 5 * hp + c) * KC, vf[c]);
    uint32_t a0, a2, a3, a1, b0, b2, b3, b1;
    softmax4(sa[0], sa[1], sa[2], p0, p1, msk, a0, a2, a3, a1);
    softmax4(sb[0], sb[1], sb[2], p0, p1, msk, b0, b2, b3, b1);
    constexpr uint32_t ONE = 0x3f803f80u;
    float o[6][4], su[2][4];
#pragma unroll
    for (int c = 0; c < 6; c++) o[c][0] = o[c][1] = o[c][2] = o[c][3] = 0.f;
#pragma unroll
    for (int c = 0; c < 2; c++) su[c][0] = su[c][1] = su[c][2] = su[c][3] = 0.f;
    mma16(su[0], a0, 0, a2, a3, ONE, ONE); mma16(su[1], b0, 0, b2, b3, ONE, ONE);
    mma8(su[0], 0, a1, ONE); mma8(su[1], 0, b1, ONE);
#pragma unroll
    for (int c = 0; c < 3; c++) {
      mma16(o[c], a0, 0, a2, a3, vf[c][0], vf[c][1]);
      mma16(o[3 + c], b0, 0, b2, b3, vf[2 + c][0], vf[2 + c][1]);
    }
#pragma unroll
    for (int c = 0; c < 3; c++) {
      mma8(o[c], 0, a1, vf[c][2]);
      mma8(o[3 + c], 0, b1, vf[2 + c][2]);
    }
    const float ral = ezl * rcp(su[0][0]), rah = ezh * rcp(su[0][2]), rbl = ezl * rcp(su[1][0]), rbh = ezh * rcp(su[1][2]);
    const float rml = t < 2 ? ral : rbl, rmh = t < 2 ? rah : rbh;
    ores[hp][0] = pack_bf16(o[0][0] * ral, o[0][1] * ral); ores[hp][1] = pack_bf16(o[0][2] * rah, o[0][3] * rah);
    ores[hp][2] = pack_bf16(o[1][0] * ral, o[1][1] * ral); ores[hp][3] = pack_bf16(o[1][2] * rah, o[1][3] * rah);
    ores[hp][4] = pack_bf16((t < 2 ? o[2][0] : o[3][0]) * rml, (t < 2 ? o[2][1] : o[3][1]) * rml);
    ores[hp][5] = pack_bf16((t < 2 ? o[2][2] : o[3][2]) * rmh, (t < 2 ? o[2][3] : o[3][3]) * rmh);
    ores[hp][6] = pack_bf16(o[4][0] * rbl, o[4][1] * rbl); ores[hp][7] = pack_bf16(o[4][2] * rbh, o[4][3] * rbh);
    ores[hp][8] = pack_bf16(o[5][0] * rbl, o[5][1] * rbl); ores[hp][9] = pack_bf16(o[5][2] * rbh, o[5][3] * rbh);
#undef QF
  }
  stsm_x4(ob, ores[0][0], ores[0][1], ores[0][2], ores[0][3]);
  stsm_x4(ob + 32, ores[0][4], ores[0][5], ores[0][6], ores[0][7]);
  stsm_x4(ob + 64, ores[0][8], ores[0][9], ores[1][0], ores[1][1]);
  stsm_x4(ob + 96, ores[1][2], ores[1][3], ores[1][4], ores[1][5]);
  stsm_x4(ob + 128, ores[1][6], ores[1][7], ores[1][8], ores[1][9]);
}

__device__ __forceinline__ void consumer(uint32_t sbase, int wg, const Role& R, const Maps& maps, const __nv_bfloat16* __restrict__ b1) {
  int tid = threadIdx.x & 127;
  const bool elect = (tid == 0);
  const uint32_t bars = sbase + OFF_BAR;
  Pipe p{0, 0, 0};
#define LANE_VARS                                                                                     \
  tid = opaque(tid);                                                                                  \
  const int warp = tid >> 5, lane = tid & 31, t = lane & 3, g = lane >> 2;                            \
  const int r16 = ((lane >> 3) & 1) * 8 + (lane & 7);                                                 \
  const int srow = wg * 64 + warp * 16 + r16;                                                         \
  const int hi = lane >> 4;                                                                           \
  (void)t; (void)g; (void)srow; (void)hi;
  {
    float acc[112];
    const int nch = R.s ? 26 : 28;
    {
      const uint32_t* bp = reinterpret_cast<const uint32_t*>(b1 + R.full0) + (tid & 3);
      const uint32_t* bq = reinterpret_cast<const uint32_t*>(b1 + R.part0) + (tid & 3);
#pragma unroll
      for (int c = 0; c < 28; c++) {
        uint32_t v = 0;
        if (c < 24) v = __ldg(bp + c * 4);
        else if (c < nch) v = __ldg(bq + (c - 24) * 4);
        acc[4 * c] = bf_lo(v); acc[4 * c + 1] = bf_hi(v); acc[4 * c + 2] = bf_lo(v); acc[4 * c + 3] = bf_hi(v);
      }
    }
    cluster_wait();
    if (tid == 0 && wg == 0) PROF(1);
    if (R.s == 0) mainloop<224, 112, false, false>(acc, 10, p, sbase, wg, elect, 0, -1);
    else mainloop<208, 112, false, false>(acc, 10, p, sbase, wg, elect, 0, -1);
    if (tid == 0) PROF3(wg ? 40 : 41); if (tid == 0 && wg == 0) PROF(2);
    LANE_VARS
    mbar_wait(bars + BAR_RQ * 8, 0);
    const uint32_t sa = sbase + OFF_STG + srow * 128;
    const int sw = srow & 7;
    auto act2 = [&](float a, float b) { uint32_t r = pack_bf16_relu(a, b); return mul_bf16x2(r, r); };
#pragma unroll
    for (int c = 0; c < 28; c += 2) {
      if (c < 26 || c < nch)
        stsm_x4(sa + (c >> 3) * 16384 + ((((c & 7) + hi) ^ sw) << 4), act2(acc[4 * c], acc[4 * c + 1]), act2(acc[4 * c + 2], acc[4 * c + 3]),
                act2(acc[4 * c + 4], acc[4 * c + 5]), act2(acc[4 * c + 6], acc[4 * c + 7]));
    }
    fence_async_smem();
    __syncwarp();
    if (lane == 0) mbar_arrive(bars + BAR_S1F * 8);
    if (tid == 0) PROF3(wg ? 42 : 43); if (tid == 0 && wg == 0) PROF(3);
  }
  {
    float acc[124];
    mainloop<248, 124, false, true>(acc, 10, p, sbase, wg, elect, 0, -1);
    if (tid == 0) PROF3(wg ? 44 : 45); if (tid == 0 && wg == 0) PROF(4);
    LANE_VARS
    if (t == 0) {
      const uint32_t ga = sbase + OFF_G + (2 * (warp * 16 + g) + wg) * 4;
      sts32f(ga, __expf(fminf(fmaxf(acc[120], -60.f), 60.f)));
      sts32f(ga + 64, __expf(fminf(fmaxf(acc[122], -60.f), 60.f)));
    }
    mbar_wait(bars + BAR_S1E * 8, 0);
    const uint32_t sq = sbase + OFF_STG + (wg * 4 + warp) * 2560 + lane * 16;
    const uint32_t sk = sbase + OFF_STG + STG_KV + wg * KPAR + (warp * 16 + 8 + r16) * 16 + hi * KC;
#pragma unroll
    for (int c = 0; c < 30; c += 2) {
      const uint32_t a = (c < 10) ? sq + c * 256 : sk + (c - 10) * KC;
      stsm_x4(a, pack_bf16(acc[4 * c], acc[4 * c + 1]), pack_bf16(acc[4 * c + 2], acc[4 * c + 3]),
              pack_bf16(acc[4 * c + 4], acc[4 * c + 5]), pack_bf16(acc[4 * c + 6], acc[4 * c + 7]));
    }
    __syncwarp();
    if (lane == 0) mbar_arrive(bars + BAR_S2F * 8);
    if (tid == 0) PROF3(wg ? 46 : 47); if (tid == 0 && wg == 0) PROF(5);
  }
  {
    float acc[80];
    const int nblk = (R.s ? 19 : 18) - NPRE;
    const bool home = (wg == R.s);
    p.sb = 3; p.pb = 0;
    mainloop<160, 80, true, true>(acc, NPRE, p, sbase, wg, elect, 0, -1);
    {
      LANE_VARS
      if (tid == 0) PROF3(wg ? 48 : 49); if (tid == 0 && wg == 0) PROF(17);
      mbar_wait(bars + BAR_HALO * 8, 0);
      if (tid == 0 && wg == 0) PROF(22);
      attention(sbase + OFF_STG, sbase + OFF_G, wg, warp, lane, R.i == 0 && warp == 0);
      fence_async_smem();
      __syncwarp();
      if (lane == 0) mbar_arrive(bars + BAR_OF * 8);
      if (tid == 0) PROF3(wg ? 50 : 51); if (tid == 0 && wg == 0) PROF(18);
    }
    mainloop<160, 80, true, false>(acc, nblk, p, sbase, wg, elect, 4, (home && LAG > 0) ? nblk - LAG : -1);
    if (tid == 0) PROF(home ? 6 : 9);
    LANE_VARS
    if (!home) {
      if (LAG > 0) bar_arrive(3, 256);
      const int partner = (R.i * 8 + R.c * 2 + (R.s ^ 1));
      uint4* d = g_part + (size_t)partner * 1280 + tid;
#pragma unroll
      for (int q = 0; q < 10; q++)
        st_relaxed4(d + q * 128, make_uint4(max(pack_bf16(acc[8 * q], acc[8 * q + 1]), 1u), max(pack_bf16(acc[8 * q + 2], acc[8 * q + 3]), 1u),
                                            max(pack_bf16(acc[8 * q + 4], acc[8 * q + 5]), 1u), max(pack_bf16(acc[8 * q + 6], acc[8 * q + 7]), 1u)));
    } else {
      uint4* src = g_part + (size_t)(R.i * 8 + R.c * 2 + R.s) * 1280 + tid;
      uint4 pv[10];
      int iter = 0;
      bool ok;
      do {
        ok = true;
#pragma unroll
        for (int q = 0; q < 10; q++) {
          pv[q] = ld_relaxed4(src + q * 128);
          ok = ok && pv[q].x && pv[q].y && pv[q].z && pv[q].w;
        }
        if (++iter > (1 << 22)) asm volatile("trap;");
      } while (!ok);
      if (tid == 0) PROF(7);
      mbar_wait(bars + BAR_S2E * 8, 0);
      const int row_lo = wg * 64 + warp * 16 + g;
      const float glo = rcp(1.f + lds32f(sbase + OFF_G + row_lo * 4)), ghi = rcp(1.f + lds32f(sbase + OFF_G + (row_lo + 8) * 4));
      const int lrow = warp * 16 + r16;
      const uint32_t so = sbase + OFF_STG + lrow * 128;
      const int sw = lrow & 7;
      const uint32_t b2a = sbase + OFF_B2 + t * 4;
#pragma unroll
      for (int q = 0; q < 10; q++) {
        const uint32_t b0 = lds32(b2a + q * 32), b1v = lds32(b2a + q * 32 + 16);
        const uint32_t x = pv[q].x, y = pv[q].y, z = pv[q].z, w = pv[q].w;
        const uint32_t r0 = pack_bf16((acc[8 * q] + bf_lo(x) + bf_lo(b0)) * glo, (acc[8 * q + 1] + bf_hi(x) + bf_hi(b0)) * glo);
        const uint32_t r1 = pack_bf16((acc[8 * q + 2] + bf_lo(y) + bf_lo(b0)) * ghi, (acc[8 * q + 3] + bf_hi(y) + bf_hi(b0)) * ghi);
        const uint32_t r2 = pack_bf16((acc[8 * q + 4] + bf_lo(z) + bf_lo(b1v)) * glo, (acc[8 * q + 5] + bf_hi(z) + bf_hi(b1v)) * glo);
        const uint32_t r3 = pack_bf16((acc[8 * q + 6] + bf_lo(w) + bf_lo(b1v)) * ghi, (acc[8 * q + 7] + bf_hi(w) + bf_hi(b1v)) * ghi);
        stsm_x4(so + (q >> 2) * 8192 + (((((2 * q) & 7) + hi) ^ sw) << 4), r0, r1, r2, r3);
        st_relaxed4(src + q * 128, make_uint4(0, 0, 0, 0));
      }
      fence_async_smem();
      bar_sync(2, 128);
      if (tid == 0) {
        const bool odd = R.c & 1;
        const int x0 = R.c * 160 + (odd ? 32 : 0), x2 = R.c * 160 + (odd ? 0 : 128), y = R.i * 128 + wg * 64;
        tma2d_store(&maps.of, sbase + OFF_STG, x0, y);
        tma2d_store(&maps.of, sbase + OFF_STG + 8192, x0 + 64, y);
        tma2d_store(&maps.on, sbase + OFF_STG + 16384, x2, y);
        bulk_commit();
        asm volatile("red.relaxed.gpu.global.add.u32 [%0], 1;" ::"l"(&g_done[0]) : "memory");
        bulk_wait_read();
        PROF(8);
      }
    }
  }
}

__device__ __forceinline__ void producer(uint32_t sbase, const Maps& maps, const Role& R,
                                         const __nv_bfloat16* w2, const __nv_bfloat16* wo) {
  const uint32_t bars = sbase + OFF_BAR;
  uint32_t na = 0, s = 0, ph = 1;
  const int jq = R.c * 2 + R.s, y0 = R.i * 128;
  {
    const CUtensorMap* ta = &maps.ax[0];
    const CUtensorMap* t0 = &maps.w1f;
    const CUtensorMap* t1 = R.rank ? &maps.w1n[R.s] : &maps.w1f;
    int x0 = R.full0 + R.rank * 64, x1 = R.rank ? R.part0 : R.full0 + 128, y = 0, xa = 0, ya = y0;
    uint32_t bytes = R.s ? 26624 : 28672;
    const uint32_t db = sbase + OFF_B + R.rank * 8192;
#pragma unroll 1
    for (int n = 0; n < 20; ++n) {
      if (n == 10) {
        PROF(14); mbar_wait(bars + BAR_RQ * 8, 0); PROF(15);
        ta = &maps.ax[1]; t0 = t1 = &maps.wq;
        x0 = R.rank * 64; x1 = x0 + 128; y = jq * DM; xa = 0; ya = R.i * 64; bytes = 32768;
      }
      const uint32_t sa = na & 3;
      if (n < 3) PROF3(109 + n * 6);
      if (n > 0) {
        mbar_wait(bars + (BAR_AE + sa) * 8, ((na >> 2) & 1) ^ 1);
        mbar_expect_tx(bars + (BAR_AF + sa) * 8, 16384);
        tma3d(sbase + OFF_A + sa * 16384, ta, bars + (BAR_AF + sa) * 8, xa, ya);
      }
      ++na;
      if (n < 3) PROF3(110 + n * 6);
      mbar_wait(bars + (BAR_BE + s) * 8, ph);
      const uint32_t fb = bars + (BAR_BF + s) * 8;
      mbar_expect_tx(fb, bytes);
      if (n < 3) PROF3(111 + n * 6);
      tma2d_mc(db + s * 32768, t0, fb, x0, y);
      if (n < 3) PROF3(112 + n * 6);
      tma2d_mc(db + s * 32768 + 16384, t1, fb, x1, y);
      if (n < 3) PROF3(113 + n * 6);
      PROF2(64 + na - 1);
      if (n < 7) {
        if (((n + 3) & 7) == jq) pf3d(ta, xa + 192, ya);
        if (((n + 3) & 7) == (R.i >> 1)) { pf2d(t0, x0, y + 192); pf2d(t1, x1, y + 192); }
      }
      if (n < 3) PROF3(114 + n * 6);
      if (n == 2) {
        mbar_expect_tx(bars + BAR_X1 * 8, 19200);
#pragma unroll 1
        for (int k = 0; k < 3; k++) tma2d(sbase + OFF_STG + k * 6400, &maps.rsrc, bars + BAR_X1 * 8, k * DM + jq * 80, R.i * 40);
      }
      if (n == 6) {
        prefetch_l2(reinterpret_cast<const uint8_t*>(w2) + blockIdx.x * 17280, 17280);
        prefetch_l2(reinterpret_cast<const uint8_t*>(wo) + blockIdx.x * 6400, 6400);
      }
      if (++s == 3) { s = 0; ph ^= 1; }
      xa += 64; y += 64;
    }
  }
  {
    const bool odd = R.c & 1;
    const int x0 = R.c * 160 + (odd ? 32 : 0), x2 = R.c * 160 + (odd ? 0 : 128);
    const CUtensorMap* tf = &maps.w2f;
    const CUtensorMap* tp = &maps.w2n;
    const int nh = R.s ? 14 : 13;
    int y = R.s ? 13 * 64 : 0, xa = DM + y;
    const uint32_t db = sbase + OFF_B + R.rank * 4096;
#pragma unroll 1
    for (int n = 0; n < nh + 5; ++n) {
      if (n == 0) { PROF(10); mbar_wait(bars + BAR_RH * 8, 0); PROF(11); }
      if (n == nh) {
        PROF(12); mbar_wait(bars + BAR_RO * 8, 0); PROF(13);
        tf = &maps.wof; tp = &maps.won;
        y = R.s * 320; xa = y;
      }
      const uint32_t sa = na & 3;
      mbar_wait(bars + (BAR_AE + sa) * 8, ((na >> 2) & 1) ^ 1);
      mbar_expect_tx(bars + (BAR_AF + sa) * 8, 16384);
      tma2d(sbase + OFF_A + sa * 16384, &maps.hf, bars + (BAR_AF + sa) * 8, xa, y0);
      ++na;
      const uint32_t sl = (n + 3) & 3;
      if (n < 3) {
        mbar_wait(bars + (BAR_BE + s) * 8, ph);
        if (++s == 3) { s = 0; ph ^= 1; }
      } else if (n >= 4) {
        mbar_wait(bars + (BAR_CE + sl) * 8, ((n >> 2) & 1) ^ 1);
      }
      const uint32_t fb = bars + (BAR_CF + sl) * 8;
      mbar_expect_tx(fb, 20480);
      const uint32_t d = db + sl * 24576;
      const int yy = y + R.rank * 32;
      tma2d_mc(d, tf, fb, x0, yy);
      tma2d_mc(d + 8192, tf, fb, x0 + 64, yy);
      tma2d_mc(d + 16384, tp, fb, x2, yy);
      PROF2(64 + na - 1);
      xa += 64; y += 64;
    }
  }
}

__device__ __forceinline__ void aux(uint32_t sbase, const Maps& maps, const Role& R,
                                    const __nv_bfloat16* __restrict__ gate_w, const __nv_bfloat16* __restrict__ b2) {
  const int lane = threadIdx.x & 31;
  const uint32_t bars = sbase + OFF_BAR;
  const uint32_t stg = sbase + OFF_STG;
  const int i = R.i, jq = R.c * 2 + R.s;
  unsigned* fl = g_flags + i * 32;
  const unsigned epoch = ld_relaxed(&g_done[0]) >> 7;
  if (lane < 20) {
    const uint32_t gv = __ldg(reinterpret_cast<const uint32_t*>(gate_w) + i * 20 + lane);
    uint4* d = reinterpret_cast<uint4*>(g_wqkv + (size_t)(jq * DM + i * 40 + 2 * lane) * 256 + 240);
    d[0] = make_uint4(gv & 0xffffu, 0, 0, 0);
    d[32] = make_uint4(gv >> 16, 0, 0, 0);
  }
#pragma unroll
  for (int k = 0; k < 3; k++) {
    const int n = (k * 32 + lane) * 2;
    if (n < 160) {
      const int col = R.c * 160 + ((R.c & 1) ? (n < 128 ? n + 32 : n - 128) : n);
      sts32(sbase + OFF_B2 + n * 2, __ldg(reinterpret_cast<const uint32_t*>(b2 + col)));
    }
  }
  cluster_wait();
  __syncwarp();
  if (lane == 0) {
    mbar_wait(bars + BAR_X1 * 8, 0);
#pragma unroll 1
    for (int k = 0; k < 3; k++) tma2d_store(&maps.rdst, stg + k * 6400, k * 80, jq * DM + i * 40);
    bulk_commit();
    bulk_wait();
    fence_async();
    red_release(g_rep + jq * 32, 1);
    PROF(21);
    wait_flag(g_rep + jq * 32, (epoch + 1) * 16);
    fence_async();
    mbar_arrive(bars + BAR_RQ * 8);
    PROF(20);
    mbar_wait(bars + BAR_S1F * 8, 0);
#pragma unroll 1
    for (int k = 0; k < 7; k++) {
      if (k < 6) tma2d_store(&maps.hs, stg + k * 8192, DM + R.full0 + (k >> 1) * 64, i * 128 + (k & 1) * 64);
      else tma2d_store(&maps.hn[R.s], stg + 49152, DM + R.part0, i * 128);
      bulk_commit();
      if (k < 6) __nanosleep(HPACE);
    }
    bulk_wait_read();
    mbar_arrive(bars + BAR_S1E * 8);
    bulk_wait();
    fence_async();
    red_release(fl + FL_H, 1);
    PROF(16);
    wait_flag(fl + FL_H, (epoch + 1) * 8);
    fence_async();
    mbar_arrive(bars + BAR_RH * 8);
  }
  __syncwarp();
  mbar_wait(bars + BAR_S2F * 8, 0);
  {
    const uint32_t hs = stg + STG_KV + (lane >> 3) * KC + (lane & 7) * 16;
    if (i < 15) {
      uint4* d = &g_halo[(i * 8 + jq) * 320 + lane];
#pragma unroll
      for (int k = 0; k < 10; k++) {
        const uint4 v = lds128(hs + k * 4 * KC + 1024);
        st_relaxed4(d + k * 32, make_uint4(max(v.x, 1u), max(v.y, 1u), max(v.z, 1u), max(v.w, 1u)));
      }
    }
    uint4 v[10];
#pragma unroll
    for (int k = 0; k < 10; k++) v[k] = make_uint4(0, 0, 0, 0);
    if (i > 0) {
      uint4* src = &g_halo[((i - 1) * 8 + jq) * 320 + lane];
      int iter = 0;
      bool ok;
      do {
        ok = true;
#pragma unroll
        for (int k = 0; k < 10; k++) {
          v[k] = ld_relaxed4(src + k * 32);
          ok = ok && v[k].x && v[k].y && v[k].z && v[k].w;
        }
        if (++iter > (1 << 22)) asm volatile("trap;");
      } while (!ok);
#pragma unroll
      for (int k = 0; k < 10; k++) st_relaxed4(src + k * 32, make_uint4(0, 0, 0, 0));
    }
#pragma unroll
    for (int k = 0; k < 10; k++) sts128(hs + k * 4 * KC, v[k]);
  }
  __syncwarp();
  if (lane == 0) {
    mbar_arrive(bars + BAR_HALO * 8);
    mbar_wait(bars + BAR_OF * 8, 0);
    tma3d_store(&maps.os, stg, jq * 80, i * 64);
    bulk_commit();
    bulk_wait_read();
    mbar_arrive(bars + BAR_S2E * 8);
    bulk_wait();
    fence_async();
    red_release(fl + FL_O, 1);
    PROF(19);
    wait_flag(fl + FL_O, (epoch + 1) * 8);
    fence_async();
    mbar_arrive(bars + BAR_RO * 8);
  }
}

__global__ void __launch_bounds__(384, 1)
fused_kernel(const __grid_constant__ Maps maps, const __nv_bfloat16* __restrict__ wo,
             const __nv_bfloat16* __restrict__ b1, const __nv_bfloat16* __restrict__ w2, const __nv_bfloat16* __restrict__ b2,
             const __nv_bfloat16* __restrict__ gate_w) {
  extern __shared__ __align__(1024) uint8_t smem_raw[];
  const uint32_t sbase = smem_u32(smem_raw);
  uint32_t rank;
  asm volatile("mov.u32 %0, %%cluster_ctarank;" : "=r"(rank));
  Role R;
  {
    const int q = blockIdx.x >> 1;
    int grp, m;
    if (q < 4) { grp = 0; m = q; }
    else if (q < 36) { grp = 1 + ((q - 4) & 7); m = (q - 4) >> 3; }
    else { grp = 9 + (q - 36) % 7; m = (q - 36) / 7; }
    R.i = (grp >> 1) * 2 + (int)rank; R.s = grp & 1; R.c = m; R.rank = (int)rank;
    R.full0 = 192 * (2 * m + R.s);
    R.part0 = R.s ? 1664 + 16 * m : 1536 + 32 * m;
  }
  const int wid = __shfl_sync(0xffffffffu, (int)(threadIdx.x >> 5), 0), lane = threadIdx.x & 31;
  const uint32_t bars = sbase + OFF_BAR;
  if (lane == 0) {
    if (wid == 8) PROF(0);
#pragma unroll 1
    for (int b = wid >= 8 ? wid - 8 : wid + 4; b < 32; b += 12) mbar_init(bars + b * 8, 1u << ((BAR_COUNTS >> (2 * b)) & 3));
    asm volatile("fence.mbarrier_init.release.cluster;" ::: "memory");
  }
  __syncwarp();
  cluster_arrive();
  if (wid >= 8) {
    asm volatile("setmaxnreg.dec.sync.aligned.u32 88;");
    if (wid == 8) {
      if (lane == 0) {
        PROF(23);
        if (sbase & 1023) asm volatile("trap;");
        mbar_expect_tx(bars + BAR_AF * 8, 16384);
        tma3d(sbase + OFF_A, &maps.ax[0], bars + BAR_AF * 8, 0, R.i * 128);
        PROF(24);
      }
      __syncwarp();
      cluster_wait();
      if (lane == 0) PROF(25);
      if (lane == 0) producer(sbase, maps, R, w2, wo);
    } else if (wid == 9) {
      aux(sbase, maps, R, gate_w, b2);
    } else {
      if (lane == 0) {
#pragma unroll 1
        for (int k = wid - 10; k < NMAPS; k += 2) prefetch_tm(&maps.ax[0] + k);
      }
      __syncwarp();
      cluster_wait();
    }
  } else {
    if (threadIdx.x == 0) PROF(27);
    asm volatile("setmaxnreg.inc.sync.aligned.u32 208;");
    if (threadIdx.x == 0) PROF(28);
    consumer(sbase, wid >> 2, R, maps, b1);
  }
}

typedef CUresult (*EncFn)(CUtensorMap*, CUtensorMapDataType, cuuint32_t, void*, const cuuint64_t*, const cuuint64_t*, const cuuint32_t*,
                          const cuuint32_t*, CUtensorMapInterleave, CUtensorMapSwizzle, CUtensorMapL2promotion, CUtensorMapFloatOOBfill);

void make_map(EncFn enc, CUtensorMap* m, const void* base, uint64_t d0, uint64_t d1, uint64_t pitch1, uint32_t b0, uint32_t b1,
              bool swz = true, uint64_t d2 = 0, uint64_t pitch2 = 0, uint32_t b2 = 1) {
  cuuint64_t dims[3] = {d0, d1, d2};
  cuuint64_t strides[2] = {pitch1, pitch2};
  cuuint32_t box[3] = {b0, b1, b2};
  cuuint32_t es[3] = {1, 1, 1};
  CUresult res = enc(m, CU_TENSOR_MAP_DATA_TYPE_BFLOAT16, d2 ? 3 : 2, const_cast<void*>(base), dims, strides, box, es,
                     CU_TENSOR_MAP_INTERLEAVE_NONE, swz ? CU_TENSOR_MAP_SWIZZLE_128B : CU_TENSOR_MAP_SWIZZLE_NONE,
                     CU_TENSOR_MAP_L2_PROMOTION_L2_128B, CU_TENSOR_MAP_FLOAT_OOB_FILL_NONE);
  (void)res;
}

}

extern "C" void kernel_launch(void* const* d_in, const int* in_sizes, int n_in, void* d_out, int out_size) {
  (void)in_sizes; (void)n_in; (void)out_size;
  const __nv_bfloat16* x = (const __nv_bfloat16*)d_in[0];
  const __nv_bfloat16* wqkv = (const __nv_bfloat16*)d_in[1];
  const __nv_bfloat16* wo = (const __nv_bfloat16*)d_in[2];
  const __nv_bfloat16* w1 = (const __nv_bfloat16*)d_in[4];
  const __nv_bfloat16* b1 = (const __nv_bfloat16*)d_in[5];
  const __nv_bfloat16* w2 = (const __nv_bfloat16*)d_in[6];
  const __nv_bfloat16* b2 = (const __nv_bfloat16*)d_in[7];
  const __nv_bfloat16* gate_w = (const __nv_bfloat16*)d_in[8];

  static EncFn enc = nullptr;
  static void* act_ptr = nullptr;
  static void* wq_ptr = nullptr;
  if (!enc) {
    void* fn = nullptr;
    cudaDriverEntryPointQueryResult qr;
    cudaGetDriverEntryPoint("cuTensorMapEncodeTiled", &fn, cudaEnableDefault, &qr);
    enc = (EncFn)fn;
    cudaGetSymbolAddress(&act_ptr, g_act);
    cudaGetSymbolAddress(&wq_ptr, g_wqkv);
    cudaFuncSetAttribute(fused_kernel, cudaFuncAttributeMaxDynamicSharedMemorySize, SMEM_TOTAL);
  }
  Maps maps;
  make_map(enc, &maps.ax[0], x, DM, SEQ, DM * 2, 64, 128, true, 1, (uint64_t)SEQ * DM * 2, 1);
  make_map(enc, &maps.ax[1], x, DM, SEQ / 2, DM * 4, 64, 64, true, 2, DM * 2, 2);
  make_map(enc, &maps.w1f, w1, FF, DM, FF * 2, 64, 64);
  make_map(enc, &maps.w1n[0], w1, FF, DM, FF * 2, 32, 64);
  make_map(enc, &maps.w1n[1], w1, FF, DM, FF * 2, 16, 64);
  make_map(enc, &maps.wq, wq_ptr, 256, 8 * DM, 512, 64, 64);
  make_map(enc, &maps.rsrc, wqkv, 3 * DM, DM, 3 * DM * 2, 80, 40, false);
  make_map(enc, &maps.rdst, wq_ptr, 240, 8 * DM, 512, 80, 40, false);
  make_map(enc, &maps.hs, act_ptr, ACT_LD, SEQ, ACT_LD * 2, 64, 64);
  make_map(enc, &maps.hn[0], act_ptr, ACT_LD, SEQ, ACT_LD * 2, 32, 128);
  make_map(enc, &maps.hn[1], act_ptr, ACT_LD, SEQ, ACT_LD * 2, 16, 128);
  make_map(enc, &maps.os, act_ptr, ACT_LD, SEQ / 2, ACT_LD * 4, 80, 64, false, 2, ACT_LD * 2, 2);
  make_map(enc, &maps.hf, act_ptr, ACT_LD, SEQ, ACT_LD * 2, 64, 128);
  make_map(enc, &maps.w2f, w2, DM, FF, DM * 2, 64, 32);
  make_map(enc, &maps.w2n, w2, DM, FF, DM * 2, 32, 32);
  make_map(enc, &maps.wof, wo, DM, DM, DM * 2, 64, 32);
  make_map(enc, &maps.won, wo, DM, DM, DM * 2, 32, 32);
  make_map(enc, &maps.of, d_out, DM, SEQ, DM * 2, 64, 64);
  make_map(enc, &maps.on, d_out, DM, SEQ, DM * 2, 32, 64);

  cudaLaunchConfig_t cfg = {};
  cfg.gridDim = dim3(128);
  cfg.blockDim = dim3(384);
  cfg.dynamicSmemBytes = SMEM_TOTAL;
  cfg.stream = cudaStreamPerThread;
  cudaLaunchAttribute attr[1];
  attr[0].id = cudaLaunchAttributeClusterDimension;
  attr[0].val.clusterDim.x = 2; attr[0].val.clusterDim.y = 1; attr[0].val.clusterDim.z = 1;
  cfg.attrs = attr; cfg.numAttrs = 1;
  cudaLaunchKernelEx(&cfg, fused_kernel, maps, wo, b1, w2, b2, gate_w);
}
```

```cpp
#include <cuda_runtime.h>
#include <cuda_bf16.h>
#include <cuda.h>
#include <stdint.h>

namespace {

constexpr int SEQ = 2048, DM = 640, FF = 1728;
constexpr int ACT_LD = DM + FF;
constexpr int OFF_A = 0;
constexpr int OFF_B = 65536;
constexpr int OFF_STG = 163840;
constexpr int STG_KV = 20480, KC = 1152, KPAR = 20 * KC;
constexpr int STG_BYTES = STG_KV + 2 * KPAR;
constexpr int OFF_BAR = OFF_STG + STG_BYTES;
constexpr int OFF_G = OFF_BAR + 256;
constexpr int OFF_B2 = OFF_G + 512;
constexpr int SMEM_TOTAL = OFF_B2 + 320;
static_assert(SMEM_TOTAL <= 232448, "smem");

#define NPRE 5
#define LAG 4
#define HPACE 400

#define TAILM 5
#define PFN 7

constexpr int BAR_AF = 0, BAR_AE = 4, BAR_BF = 8, BAR_BE = 11, BAR_CF = 14, BAR_CE = 18, BAR_S1F = 22, BAR_S1E = 23, BAR_S2F = 24,
              BAR_HALO = 25, BAR_OF = 26, BAR_S2E = 27, BAR_RQ = 28, BAR_RH = 29, BAR_RO = 30, NBARS = 31;

constexpr unsigned long long bar_counts() {
  unsigned long long k = 0;
  for (int b = 0; b < 32; b++) {
    const int e = (b >= BAR_AE && b < BAR_BF) ? 1 : ((b >= BAR_BE && b < BAR_CF) || (b >= BAR_CE && b < BAR_S1F)) ? 2
                  : (b == BAR_S1F || b == BAR_S2F || b == BAR_OF) ? 3 : 0;
    k |= (unsigned long long)e << (2 * b);
  }
  return k;
}
constexpr unsigned long long BAR_COUNTS = bar_counts();

constexpr int FL_H = 0, FL_O = 1;

struct Maps {
  CUtensorMap ax[2];
  CUtensorMap w1f, w1n[2];
  CUtensorMap wq;
  CUtensorMap hs, hn[2];
  CUtensorMap os;
  CUtensorMap hf;
  CUtensorMap w2f, w2n, wof, won;
  CUtensorMap of, on;
};
constexpr int NMAPS = sizeof(Maps) / sizeof(CUtensorMap);

__device__ __nv_bfloat16 g_act[SEQ * ACT_LD];
__device__ __nv_bfloat16 g_wqkv[8 * DM * 256];
__device__ uint4 g_halo[16 * 8 * 320];
__device__ unsigned g_flags[16 * 32];
__device__ unsigned g_rep[8 * 32];
__device__ unsigned g_done[32];
#define PROF3(slot) do { } while (0)
#define PROF2(slot) do { } while (0)
#define PROF(slot) do { } while (0)
#define PROFV(idx, val) do { } while (0)
#define PROFML(outp) 0
constexpr int SMEM_LAUNCH = SMEM_TOTAL;
static_assert(SMEM_LAUNCH <= 232448, "smem");

__device__ __forceinline__ long long gtime() { long long t; asm volatile("mov.u64 %0, %%globaltimer;" : "=l"(t)); return t; }
__device__ __forceinline__ uint32_t smem_u32(const void* p) { return (uint32_t)__cvta_generic_to_shared(p); }
__device__ __forceinline__ void mbar_init(uint32_t bar, uint32_t cnt) { asm volatile("mbarrier.init.shared::cta.b64 [%0], %1;" ::"r"(bar), "r"(cnt) : "memory"); }
__device__ __forceinline__ void mbar_expect_tx(uint32_t bar, uint32_t bytes) { asm volatile("mbarrier.arrive.expect_tx.shared::cta.b64 _, [%0], %1;" ::"r"(bar), "r"(bytes) : "memory"); }
__device__ __forceinline__ void mbar_wait(uint32_t bar, uint32_t parity) {
  asm volatile(
      "{\n.reg .pred p;\n.reg .u32 c;\nmov.u32 c, 0;\n"
      "LAB_WAIT:\n"
      "mbarrier.try_wait.parity.shared::cta.b64 p, [%0], %1;\n"
      "@p bra DONE;\n"
      "add.u32 c, c, 1;\n"
      "setp.lt.u32 p, c, 0x4000000;\n"
      "@p bra LAB_WAIT;\n"
      "trap;\n"
      "DONE:\n}" ::"r"(bar), "r"(parity) : "memory");
}
__device__ __forceinline__ void mbar_arrive(uint32_t bar) { asm volatile("mbarrier.arrive.shared::cta.b64 _, [%0];" ::"r"(bar) : "memory"); }
__device__ __forceinline__ void mbar_arrive_cluster(uint32_t bar, uint32_t cta) {
  asm volatile("{\n.reg .b32 ra;\nmapa.shared::cluster.u32 ra, %0, %1;\nmbarrier.arrive.shared::cluster.b64 _, [ra];\n}" ::"r"(bar), "r"(cta) : "memory");
}
__device__ __forceinline__ void tma2d(uint32_t dst, const CUtensorMap* tm, uint32_t bar, int c0, int c1) {
  asm volatile("cp.async.bulk.tensor.2d.shared::cluster.global.mbarrier::complete_tx::bytes [%0], [%1, {%3, %4}], [%2];"
               ::"r"(dst), "l"(tm), "r"(bar), "r"(c0), "r"(c1) : "memory");
}
__device__ __forceinline__ void tma3d(uint32_t dst, const CUtensorMap* tm, uint32_t bar, int c0, int c1) {
  asm volatile("cp.async.bulk.tensor.3d.shared::cluster.global.mbarrier::complete_tx::bytes [%0], [%1, {%3, %4, %5}], [%2];"
               ::"r"(dst), "l"(tm), "r"(bar), "r"(c0), "r"(c1), "r"(0) : "memory");
}
__device__ __forceinline__ void tma2d_mc(uint32_t dst, const CUtensorMap* tm, uint32_t bar, int c0, int c1) {
  asm volatile("cp.async.bulk.tensor.2d.shared::cluster.global.mbarrier::complete_tx::bytes.multicast::cluster [%0], [%1, {%3, %4}], [%2], %5;"
               ::"r"(dst), "l"(tm), "r"(bar), "r"(c0), "r"(c1), "h"((uint16_t)3) : "memory");
}
__device__ __forceinline__ void tma2d_store(const CUtensorMap* tm, uint32_t src, int c0, int c1) {
  asm volatile("cp.async.bulk.tensor.2d.global.shared::cta.bulk_group [%0, {%2, %3}], [%1];" ::"l"(tm), "r"(src), "r"(c0), "r"(c1) : "memory");
}
__device__ __forceinline__ void tma2d_reduce(const CUtensorMap* tm, uint32_t src, int c0, int c1) {
  asm volatile("cp.reduce.async.bulk.tensor.2d.global.shared::cta.add.tile.bulk_group [%0, {%2, %3}], [%1];" ::"l"(tm), "r"(src), "r"(c0), "r"(c1) : "memory");
}
__device__ __forceinline__ void tma3d_store(const CUtensorMap* tm, uint32_t src, int c0, int c1) {
  asm volatile("cp.async.bulk.tensor.3d.global.shared::cta.bulk_group [%0, {%2, %3, %4}], [%1];" ::"l"(tm), "r"(src), "r"(c0), "r"(c1), "r"(0) : "memory");
}
__device__ __forceinline__ void pf2d(const CUtensorMap* tm, int c0, int c1) {
  asm volatile("cp.async.bulk.prefetch.tensor.2d.L2.global [%0, {%1, %2}];" ::"l"(tm), "r"(c0), "r"(c1) : "memory");
}
__device__ __forceinline__ void pf3d(const CUtensorMap* tm, int c0, int c1) {
  asm volatile("cp.async.bulk.prefetch.tensor.3d.L2.global [%0, {%1, %2, %3}];" ::"l"(tm), "r"(c0), "r"(c1), "r"(0) : "memory");
}
__device__ __forceinline__ void bulk_commit() { asm volatile("cp.async.bulk.commit_group;" ::: "memory"); }
__device__ __forceinline__ void bulk_wait_read() { asm volatile("cp.async.bulk.wait_group.read 0;" ::: "memory"); }
__device__ __forceinline__ void bulk_wait() { asm volatile("cp.async.bulk.wait_group 0;" ::: "memory"); }
__device__ __forceinline__ void prefetch_tm(const CUtensorMap* tm) { asm volatile("prefetch.tensormap [%0];" ::"l"(tm) : "memory"); }
__device__ __forceinline__ void prefetch_l2(const void* p, uint32_t bytes) { asm volatile("cp.async.bulk.prefetch.L2.global [%0], %1;" ::"l"(p), "r"(bytes) : "memory"); }
__device__ __forceinline__ unsigned ld_relaxed(const unsigned* p) { unsigned v; asm volatile("ld.relaxed.gpu.global.u32 %0, [%1];" : "=r"(v) : "l"(p) : "memory"); return v; }
__device__ __forceinline__ uint4 ld_relaxed4(const uint4* p) {
  uint4 v; asm volatile("ld.relaxed.gpu.global.v4.u32 {%0,%1,%2,%3}, [%4];" : "=r"(v.x), "=r"(v.y), "=r"(v.z), "=r"(v.w) : "l"(p) : "memory"); return v;
}
__device__ __forceinline__ void st_relaxed4(uint4* p, uint4 v) {
  asm volatile("st.relaxed.gpu.global.v4.u32 [%0], {%1,%2,%3,%4};" ::"l"(p), "r"(v.x), "r"(v.y), "r"(v.z), "r"(v.w) : "memory");
}
__device__ __forceinline__ uint4 ld_relaxed128(const uint4* p) {
  uint4 v;
  asm volatile("{\n.reg .b128 t;\n.reg .b64 a, b;\nld.relaxed.gpu.global.b128 t, [%4];\nmov.b128 {a, b}, t;\nmov.b64 {%0, %1}, a;\nmov.b64 {%2, %3}, b;\n}"
               : "=r"(v.x), "=r"(v.y), "=r"(v.z), "=r"(v.w) : "l"(p) : "memory");
  return v;
}
__device__ __forceinline__ void st_relaxed128(uint4* p, uint4 v) {
  asm volatile("{\n.reg .b128 t;\n.reg .b64 a, b;\nmov.b64 a, {%1, %2};\nmov.b64 b, {%3, %4};\nmov.b128 t, {a, b};\nst.relaxed.gpu.global.b128 [%0], t;\n}"
               ::"l"(p), "r"(v.x), "r"(v.y), "r"(v.z), "r"(v.w) : "memory");
}
__device__ __forceinline__ void red_release(unsigned* p, unsigned v) { asm volatile("red.release.gpu.global.add.u32 [%0], %1;" ::"l"(p), "r"(v) : "memory"); }
__device__ __forceinline__ void wait_flag(const unsigned* p, unsigned target) {
  asm volatile(
      "{\n.reg .pred p;\n.reg .u32 c, v;\nmov.u32 c, 0;\n"
      "LAB_WAIT:\n"
      "ld.acquire.gpu.global.u32 v, [%0];\n"
      "sub.u32 v, v, %1;\n"
      "setp.ge.s32 p, v, 0;\n"
      "@p bra DONE;\n"
      "add.u32 c, c, 1;\n"
      "setp.lt.u32 p, c, 0x2000000;\n"
      "@p bra LAB_WAIT;\n"
      "trap;\n"
      "DONE:\n}" ::"l"(p), "r"(target) : "memory");
}
__device__ __forceinline__ bool elect_one() {
  uint32_t p;
  asm volatile("{\n.reg .pred P;\nelect.sync _|P, 0xffffffff;\nselp.u32 %0, 1, 0, P;\n}" : "=r"(p));
  return p != 0;
}
__device__ __forceinline__ uint4 ldg_stream(const void* p) {
  uint4 v; asm volatile("ld.global.nc.L1::no_allocate.v4.u32 {%0,%1,%2,%3}, [%4];" : "=r"(v.x), "=r"(v.y), "=r"(v.z), "=r"(v.w) : "l"(p)); return v;
}
__device__ __forceinline__ int opaque(int x) { asm volatile("" : "+r"(x)); return x; }
__device__ __forceinline__ void bar_sync(int id, int n) { asm volatile("bar.sync %0, %1;" ::"r"(id), "r"(n) : "memory"); }
__device__ __forceinline__ void bar_arrive(int id, int n) { asm volatile("bar.arrive %0, %1;" ::"r"(id), "r"(n) : "memory"); }
__device__ __forceinline__ void fence_async() { asm volatile("fence.proxy.async.global;" ::: "memory"); }
__device__ __forceinline__ void fence_async_smem() { asm volatile("fence.proxy.async.shared::cta;" ::: "memory"); }
__device__ __forceinline__ void cluster_arrive() { asm volatile("barrier.cluster.arrive.relaxed.aligned;" ::: "memory"); }
__device__ __forceinline__ void cluster_wait() { asm volatile("barrier.cluster.wait.aligned;" ::: "memory"); }
__device__ __forceinline__ uint64_t mkdesc(uint32_t addr, uint32_t lbo, uint32_t sbo) {
  return (uint64_t)((addr & 0x3FFFF) >> 4) | ((uint64_t)(lbo >> 4) << 16) | ((uint64_t)(sbo >> 4) << 32) | (1ull << 62);
}
__device__ __forceinline__ uint32_t pack_bf16(float lo, float hi) { uint32_t r; asm("cvt.rn.bf16x2.f32 %0, %1, %2;" : "=r"(r) : "f"(hi), "f"(lo)); return r; }
__device__ __forceinline__ uint32_t pack_bf16_relu(float lo, float hi) { uint32_t r; asm("cvt.rn.relu.bf16x2.f32 %0, %1, %2;" : "=r"(r) : "f"(hi), "f"(lo)); return r; }
__device__ __forceinline__ uint32_t mul_bf16x2(uint32_t a, uint32_t b) { uint32_t r; asm("mul.rn.bf16x2 %0, %1, %2;" : "=r"(r) : "r"(a), "r"(b)); return r; }
__device__ __forceinline__ uint32_t add_bf16x2(uint32_t a, uint32_t b) { uint32_t r; asm("add.rn.bf16x2 %0, %1, %2;" : "=r"(r) : "r"(a), "r"(b)); return r; }
__device__ __forceinline__ float bf_lo(uint32_t v) { return __uint_as_float(v << 16); }
__device__ __forceinline__ float bf_hi(uint32_t v) { return __uint_as_float(v & 0xffff0000u); }
__device__ __forceinline__ void stsm_x4(uint32_t a, uint32_t r0, uint32_t r1, uint32_t r2, uint32_t r3) {
  asm volatile("stmatrix.sync.aligned.m8n8.x4.shared.b16 [%0], {%1, %2, %3, %4};" ::"r"(a), "r"(r0), "r"(r1), "r"(r2), "r"(r3) : "memory");
}
__device__ __forceinline__ void ldsm_x4(uint32_t a, uint32_t (&r)[4]) {
  asm volatile("ldmatrix.sync.aligned.m8n8.x4.shared.b16 {%0, %1, %2, %3}, [%4];" : "=r"(r[0]), "=r"(r[1]), "=r"(r[2]), "=r"(r[3]) : "r"(a) : "memory");
}
__device__ __forceinline__ void ldsm_x4_t(uint32_t a, uint32_t (&r)[4]) {
  asm volatile("ldmatrix.sync.aligned.m8n8.x4.trans.shared.b16 {%0, %1, %2, %3}, [%4];" : "=r"(r[0]), "=r"(r[1]), "=r"(r[2]), "=r"(r[3]) : "r"(a) : "memory");
}
__device__ __forceinline__ void mma16(float (&d)[4], uint32_t a0, uint32_t a1, uint32_t a2, uint32_t a3, uint32_t b0, uint32_t b1) {
  asm volatile("mma.sync.aligned.m16n8k16.row.col.f32.bf16.bf16.f32 {%0,%1,%2,%3}, {%4,%5,%6,%7}, {%8,%9}, {%0,%1,%2,%3};"
               : "+f"(d[0]), "+f"(d[1]), "+f"(d[2]), "+f"(d[3]) : "r"(a0), "r"(a1), "r"(a2), "r"(a3), "r"(b0), "r"(b1));
}
__device__ __forceinline__ void mma8(float (&d)[4], uint32_t a0, uint32_t a1, uint32_t b0) {
  asm volatile("mma.sync.aligned.m16n8k8.row.col.f32.bf16.bf16.f32 {%0,%1,%2,%3}, {%4,%5}, {%6}, {%0,%1,%2,%3};"
               : "+f"(d[0]), "+f"(d[1]), "+f"(d[2]), "+f"(d[3]) : "r"(a0), "r"(a1), "r"(b0));
}
__device__ __forceinline__ uint4 lds128(uint32_t a) { uint4 v; asm volatile("ld.shared.v4.u32 {%0,%1,%2,%3}, [%4];" : "=r"(v.x), "=r"(v.y), "=r"(v.z), "=r"(v.w) : "r"(a) : "memory"); return v; }
__device__ __forceinline__ void sts128(uint32_t a, uint4 v) { asm volatile("st.shared.v4.u32 [%0], {%1,%2,%3,%4};" ::"r"(a), "r"(v.x), "r"(v.y), "r"(v.z), "r"(v.w) : "memory"); }
__device__ __forceinline__ void sts32(uint32_t a, uint32_t v) { asm volatile("st.shared.u32 [%0], %1;" ::"r"(a), "r"(v) : "memory"); }
__device__ __forceinline__ void sts32f(uint32_t a, float v) { asm volatile("st.shared.f32 [%0], %1;" ::"r"(a), "f"(v) : "memory"); }
__device__ __forceinline__ uint32_t lds32(uint32_t a) { uint32_t v; asm volatile("ld.shared.u32 %0, [%1];" : "=r"(v) : "r"(a) : "memory"); return v; }
__device__ __forceinline__ float lds32f(uint32_t a) { float v; asm volatile("ld.shared.f32 %0, [%1];" : "=f"(v) : "r"(a) : "memory"); return v; }
__device__ __forceinline__ float ex2(float x) { float r; asm("ex2.approx.ftz.f32 %0, %1;" : "=f"(r) : "f"(x)); return r; }
__device__ __forceinline__ float rcp(float x) { float r; asm("rcp.approx.ftz.f32 %0, %1;" : "=f"(r) : "f"(x)); return r; }

template <int M> __device__ __forceinline__ void wgmma_n160(float (&d)[M], uint64_t da, uint64_t db, int scale_d) {
  asm volatile("{\n.reg .pred p;\nsetp.ne.b32 p, %82, 0;\n"
    "wgmma.mma_async.sync.aligned.m64n160k16.f32.bf16.bf16 "
    "{%0, %1, %2, %3, %4, %5, %6, %7, %8, %9, %10, %11, %12, %13, %14, %15, "
    "%16, %17, %18, %19, %20, %21, %22, %23, %24, %25, %26, %27, %28, %29, %30, %31, "
    "%32, %33, %34, %35, %36, %37, %38, %39, %40, %41, %42, %43, %44, %45, %46, %47, "
    "%48, %49, %50, %51, %52, %53, %54, %55, %56, %57, %58, %59, %60, %61, %62, %63, "
    "%64, %65, %66, %67, %68, %69, %70, %71, %72, %73, %74, %75, %76, %77, %78, %79}, "
    "%80, %81, p, 1, 1, 0, 1;\n}\n"
    : "+f"(d[0]), "+f"(d[1]), "+f"(d[2]), "+f"(d[3]), "+f"(d[4]), "+f"(d[5]), "+f"(d[6]), "+f"(d[7]),
      "+f"(d[8]), "+f"(d[9]), "+f"(d[10]), "+f"(d[11]), "+f"(d[12]), "+f"(d[13]), "+f"(d[14]), "+f"(d[15]),
      "+f"(d[16]), "+f"(d[17]), "+f"(d[18]), "+f"(d[19]), "+f"(d[20]), "+f"(d[21]), "+f"(d[22]), "+f"(d[23]),
      "+f"(d[24]), "+f"(d[25]), "+f"(d[26]), "+f"(d[27]), "+f"(d[28]), "+f"(d[29]), "+f"(d[30]), "+f"(d[31]),
      "+f"(d[32]), "+f"(d[33]), "+f"(d[34]), "+f"(d[35]), "+f"(d[36]), "+f"(d[37]), "+f"(d[38]), "+f"(d[39]),
      "+f"(d[40]), "+f"(d[41]), "+f"(d[42]), "+f"(d[43]), "+f"(d[44]), "+f"(d[45]), "+f"(d[46]), "+f"(d[47]),
      "+f"(d[48]), "+f"(d[49]), "+f"(d[50]), "+f"(d[51]), "+f"(d[52]), "+f"(d[53]), "+f"(d[54]), "+f"(d[55]),
      "+f"(d[56]), "+f"(d[57]), "+f"(d[58]), "+f"(d[59]), "+f"(d[60]), "+f"(d[61]), "+f"(d[62]), "+f"(d[63]),
      "+f"(d[64]), "+f"(d[65]), "+f"(d[66]), "+f"(d[67]), "+f"(d[68]), "+f"(d[69]), "+f"(d[70]), "+f"(d[71]),
      "+f"(d[72]), "+f"(d[73]), "+f"(d[74]), "+f"(d[75]), "+f"(d[76]), "+f"(d[77]), "+f"(d[78]), "+f"(d[79])
    : "l"(da), "l"(db), "r"(scale_d));
}
template <int M> __device__ __forceinline__ void wgmma_n208(float (&d)[M], uint64_t da, uint64_t db, int scale_d) {
  asm volatile("{\n.reg .pred p;\nsetp.ne.b32 p, %106, 0;\n"
    "wgmma.mma_async.sync.aligned.m64n208k16.f32.bf16.bf16 "
    "{%0, %1, %2, %3, %4, %5, %6, %7, %8, %9, %10, %11, %12, %13, %14, %15, "
    "%16, %17, %18, %19, %20, %21, %22, %23, %24, %25, %26, %27, %28, %29, %30, %31, "
    "%32, %33, %34, %35, %36, %37, %38, %39, %40, %41, %42, %43, %44, %45, %46, %47, "
    "%48, %49, %50, %51, %52, %53, %54, %55, %56, %57, %58, %59, %60, %61, %62, %63, "
    "%64, %65, %66, %67, %68, %69, %70, %71, %72, %73, %74, %75, %76, %77, %78, %79, "
    "%80, %81, %82, %83, %84, %85, %86, %87, %88, %89, %90, %91, %92, %93, %94, %95, "
    "%96, %97, %98, %99, %100, %101, %102, %103}, "
    "%104, %105, p, 1, 1, 0, 1;\n}\n"
    : "+f"(d[0]), "+f"(d[1]), "+f"(d[2]), "+f"(d[3]), "+f"(d[4]), "+f"(d[5]), "+f"(d[6]), "+f"(d[7]),
      "+f"(d[8]), "+f"(d[9]), "+f"(d[10]), "+f"(d[11]), "+f"(d[12]), "+f"(d[13]), "+f"(d[14]), "+f"(d[15]),
      "+f"(d[16]), "+f"(d[17]), "+f"(d[18]), "+f"(d[19]), "+f"(d[20]), "+f"(d[21]), "+f"(d[22]), "+f"(d[23]),
      "+f"(d[24]), "+f"(d[25]), "+f"(d[26]), "+f"(d[27]), "+f"(d[28]), "+f"(d[29]), "+f"(d[30]), "+f"(d[31]),
      "+f"(d[32]), "+f"(d[33]), "+f"(d[34]), "+f"(d[35]), "+f"(d[36]), "+f"(d[37]), "+f"(d[38]), "+f"(d[39]),
      "+f"(d[40]), "+f"(d[41]), "+f"(d[42]), "+f"(d[43]), "+f"(d[44]), "+f"(d[45]), "+f"(d[46]), "+f"(d[47]),
      "+f"(d[48]), "+f"(d[49]), "+f"(d[50]), "+f"(d[51]), "+f"(d[52]), "+f"(d[53]), "+f"(d[54]), "+f"(d[55]),
      "+f"(d[56]), "+f"(d[57]), "+f"(d[58]), "+f"(d[59]), "+f"(d[60]), "+f"(d[61]), "+f"(d[62]), "+f"(d[63]),
      "+f"(d[64]), "+f"(d[65]), "+f"(d[66]), "+f"(d[67]), "+f"(d[68]), "+f"(d[69]), "+f"(d[70]), "+f"(d[71]),
      "+f"(d[72]), "+f"(d[73]), "+f"(d[74]), "+f"(d[75]), "+f"(d[76]), "+f"(d[77]), "+f"(d[78]), "+f"(d[79]),
      "+f"(d[80]), "+f"(d[81]), "+f"(d[82]), "+f"(d[83]), "+f"(d[84]), "+f"(d[85]), "+f"(d[86]), "+f"(d[87]),
      "+f"(d[88]), "+f"(d[89]), "+f"(d[90]), "+f"(d[91]), "+f"(d[92]), "+f"(d[93]), "+f"(d[94]), "+f"(d[95]),
      "+f"(d[96]), "+f"(d[97]), "+f"(d[98]), "+f"(d[99]), "+f"(d[100]), "+f"(d[101]), "+f"(d[102]), "+f"(d[103])
    : "l"(da), "l"(db), "r"(scale_d));
}
template <int M> __device__ __forceinline__ void wgmma_n224(float (&d)[M], uint64_t da, uint64_t db, int scale_d) {
  asm volatile("{\n.reg .pred p;\nsetp.ne.b32 p, %114, 0;\n"
    "wgmma.mma_async.sync.aligned.m64n224k16.f32.bf16.bf16 "
    "{%0, %1, %2, %3, %4, %5, %6, %7, %8, %9, %10, %11, %12, %13, %14, %15, "
    "%16, %17, %18, %19, %20, %21, %22, %23, %24, %25, %26, %27, %28, %29, %30, %31, "
    "%32, %33, %34, %35, %36, %37, %38, %39, %40, %41, %42, %43, %44, %45, %46, %47, "
    "%48, %49, %50, %51, %52, %53, %54, %55, %56, %57, %58, %59, %60, %61, %62, %63, "
    "%64, %65, %66, %67, %68, %69, %70, %71, %72, %73, %74, %75, %76, %77, %78, %79, "
    "%80, %81, %82, %83, %84, %85, %86, %87, %88, %89, %90, %91, %92, %93, %94, %95, "
    "%96, %97, %98, %99, %100, %101, %102, %103, %104, %105, %106, %107, %108, %109, %110, %111}, "
    "%112, %113, p, 1, 1, 0, 1;\n}\n"
    : "+f"(d[0]), "+f"(d[1]), "+f"(d[2]), "+f"(d[3]), "+f"(d[4]), "+f"(d[5]), "+f"(d[6]), "+f"(d[7]),
      "+f"(d[8]), "+f"(d[9]), "+f"(d[10]), "+f"(d[11]), "+f"(d[12]), "+f"(d[13]), "+f"(d[14]), "+f"(d[15]),
      "+f"(d[16]), "+f"(d[17]), "+f"(d[18]), "+f"(d[19]), "+f"(d[20]), "+f"(d[21]), "+f"(d[22]), "+f"(d[23]),
      "+f"(d[24]), "+f"(d[25]), "+f"(d[26]), "+f"(d[27]), "+f"(d[28]), "+f"(d[29]), "+f"(d[30]), "+f"(d[31]),
      "+f"(d[32]), "+f"(d[33]), "+f"(d[34]), "+f"(d[35]), "+f"(d[36]), "+f"(d[37]), "+f"(d[38]), "+f"(d[39]),
      "+f"(d[40]), "+f"(d[41]), "+f"(d[42]), "+f"(d[43]), "+f"(d[44]), "+f"(d[45]), "+f"(d[46]), "+f"(d[47]),
      "+f"(d[48]), "+f"(d[49]), "+f"(d[50]), "+f"(d[51]), "+f"(d[52]), "+f"(d[53]), "+f"(d[54]), "+f"(d[55]),
      "+f"(d[56]), "+f"(d[57]), "+f"(d[58]), "+f"(d[59]), "+f"(d[60]), "+f"(d[61]), "+f"(d[62]), "+f"(d[63]),
      "+f"(d[64]), "+f"(d[65]), "+f"(d[66]), "+f"(d[67]), "+f"(d[68]), "+f"(d[69]), "+f"(d[70]), "+f"(d[71]),
      "+f"(d[72]), "+f"(d[73]), "+f"(d[74]), "+f"(d[75]), "+f"(d[76]), "+f"(d[77]), "+f"(d[78]), "+f"(d[79]),
      "+f"(d[80]), "+f"(d[81]), "+f"(d[82]), "+f"(d[83]), "+f"(d[84]), "+f"(d[85]), "+f"(d[86]), "+f"(d[87]),
      "+f"(d[88]), "+f"(d[89]), "+f"(d[90]), "+f"(d[91]), "+f"(d[92]), "+f"(d[93]), "+f"(d[94]), "+f"(d[95]),
      "+f"(d[96]), "+f"(d[97]), "+f"(d[98]), "+f"(d[99]), "+f"(d[100]), "+f"(d[101]), "+f"(d[102]), "+f"(d[103]),
      "+f"(d[104]), "+f"(d[105]), "+f"(d[106]), "+f"(d[107]), "+f"(d[108]), "+f"(d[109]), "+f"(d[110]), "+f"(d[111])
    : "l"(da), "l"(db), "r"(scale_d));
}
template <int M> __device__ __forceinline__ void wgmma_n248(float (&d)[M], uint64_t da, uint64_t db, int scale_d) {
  asm volatile("{\n.reg .pred p;\nsetp.ne.b32 p, %126, 0;\n"
    "wgmma.mma_async.sync.aligned.m64n248k16.f32.bf16.bf16 "
    "{%0, %1, %2, %3, %4, %5, %6, %7, %8, %9, %10, %11, %12, %13, %14, %15, "
    "%16, %17, %18, %19, %20, %21, %22, %23, %24, %25, %26, %27, %28, %29, %30, %31, "
    "%32, %33, %34, %35, %36, %37, %38, %39, %40, %41, %42, %43, %44, %45, %46, %47, "
    "%48, %49, %50, %51, %52, %53, %54, %55, %56, %57, %58, %59, %60, %61, %62, %63, "
    "%64, %65, %66, %67, %68, %69, %70, %71, %72, %73, %74, %75, %76, %77, %78, %79, "
    "%80, %81, %82, %83, %84, %85, %86, %87, %88, %89, %90, %91, %92, %93, %94, %95, "
    "%96, %97, %98, %99, %100, %101, %102, %103, %104, %105, %106, %107, %108, %109, %110, %111, "
    "%112, %113, %114, %115, %116, %117, %118, %119, %120, %121, %122, %123}, "
    "%124, %125, p, 1, 1, 0, 1;\n}\n"
    : "+f"(d[0]), "+f"(d[1]), "+f"(d[2]), "+f"(d[3]), "+f"(d[4]), "+f"(d[5]), "+f"(d[6]), "+f"(d[7]),
      "+f"(d[8]), "+f"(d[9]), "+f"(d[10]), "+f"(d[11]), "+f"(d[12]), "+f"(d[13]), "+f"(d[14]), "+f"(d[15]),
      "+f"(d[16]), "+f"(d[17]), "+f"(d[18]), "+f"(d[19]), "+f"(d[20]), "+f"(d[21]), "+f"(d[22]), "+f"(d[23]),
      "+f"(d[24]), "+f"(d[25]), "+f"(d[26]), "+f"(d[27]), "+f"(d[28]), "+f"(d[29]), "+f"(d[30]), "+f"(d[31]),
      "+f"(d[32]), "+f"(d[33]), "+f"(d[34]), "+f"(d[35]), "+f"(d[36]), "+f"(d[37]), "+f"(d[38]), "+f"(d[39]),
      "+f"(d[40]), "+f"(d[41]), "+f"(d[42]), "+f"(d[43]), "+f"(d[44]), "+f"(d[45]), "+f"(d[46]), "+f"(d[47]),
      "+f"(d[48]), "+f"(d[49]), "+f"(d[50]), "+f"(d[51]), "+f"(d[52]), "+f"(d[53]), "+f"(d[54]), "+f"(d[55]),
      "+f"(d[56]), "+f"(d[57]), "+f"(d[58]), "+f"(d[59]), "+f"(d[60]), "+f"(d[61]), "+f"(d[62]), "+f"(d[63]),
      "+f"(d[64]), "+f"(d[65]), "+f"(d[66]), "+f"(d[67]), "+f"(d[68]), "+f"(d[69]), "+f"(d[70]), "+f"(d[71]),
      "+f"(d[72]), "+f"(d[73]), "+f"(d[74]), "+f"(d[75]), "+f"(d[76]), "+f"(d[77]), "+f"(d[78]), "+f"(d[79]),
      "+f"(d[80]), "+f"(d[81]), "+f"(d[82]), "+f"(d[83]), "+f"(d[84]), "+f"(d[85]), "+f"(d[86]), "+f"(d[87]),
      "+f"(d[88]), "+f"(d[89]), "+f"(d[90]), "+f"(d[91]), "+f"(d[92]), "+f"(d[93]), "+f"(d[94]), "+f"(d[95]),
      "+f"(d[96]), "+f"(d[97]), "+f"(d[98]), "+f"(d[99]), "+f"(d[100]), "+f"(d[101]), "+f"(d[102]), "+f"(d[103]),
      "+f"(d[104]), "+f"(d[105]), "+f"(d[106]), "+f"(d[107]), "+f"(d[108]), "+f"(d[109]), "+f"(d[110]), "+f"(d[111]),
      "+f"(d[112]), "+f"(d[113]), "+f"(d[114]), "+f"(d[115]), "+f"(d[116]), "+f"(d[117]), "+f"(d[118]), "+f"(d[119]),
      "+f"(d[120]), "+f"(d[121]), "+f"(d[122]), "+f"(d[123])
    : "l"(da), "l"(db), "r"(scale_d));
}

template <int N> __device__ __forceinline__ void reg_fence(float (&d)[N]) {
#pragma unroll
  for (int x = 0; x < N; x++) asm volatile("" : "+f"(d[x])::"memory");
}
template <int N, int M> __device__ __forceinline__ void wg_mma(float (&d)[M], uint64_t da, uint64_t db, int sc) {
  if constexpr (N == 160) wgmma_n160(d, da, db, sc);
  else if constexpr (N == 208) wgmma_n208(d, da, db, sc);
  else if constexpr (N == 224) wgmma_n224(d, da, db, sc);
  else wgmma_n248(d, da, db, sc);
}

struct Pipe { uint32_t na, sb, pb; };

template <int N, int M, bool OUTP, bool FIN>
__device__ __forceinline__ void mainloop(float (&acc)[M], int nblk, Pipe& p, uint32_t sbase, int wg, bool elect, bool zero, int norel, int hold) {
  const uint32_t bars = sbase + OFF_BAR;
  constexpr uint32_t BSLOT = OUTP ? 24576 : 32768;
  constexpr int FULL = OUTP ? BAR_CF : BAR_BF, EMPTY = OUTP ? BAR_CE : BAR_BE;
  const uint64_t dA0 = mkdesc(sbase + OFF_A + wg * 8192, 16, 1024);
  const uint64_t dB0 = mkdesc(sbase + OFF_B, 8192, 1024);
  uint32_t prevA = 0, prevB = 0;
  reg_fence(acc);
#pragma unroll 1
  for (int kb = 0; kb < nblk; ++kb) {
    if (kb == hold) {
      asm volatile("wgmma.wait_group.sync.aligned 0;" ::: "memory");
      if (elect && prevA) { mbar_arrive(prevA); mbar_arrive_cluster(prevB, 0); mbar_arrive_cluster(prevB, 1); }
      prevA = 0;
      bar_sync(3, 256);
    }
    const uint32_t sa = p.na & 3;
    mbar_wait(bars + (BAR_AF + sa) * 8, (p.na >> 2) & 1);
    if (PROFML(OUTP) && elect && wg == 0 && p.na == 0) PROF(29);
    mbar_wait(bars + (FULL + p.sb) * 8, p.pb);
    if (PROFML(OUTP) && elect && wg == 0) PROF2(p.na);
    if (PROFML(OUTP) && elect && wg == 1) PROF3(p.na);
    const uint64_t da = dA0 + (uint64_t)(sa * 1024);
    const uint64_t db = dB0 + (uint64_t)(p.sb * (BSLOT >> 4));
    reg_fence(acc);
    asm volatile("wgmma.fence.sync.aligned;" ::: "memory");
    wg_mma<N>(acc, da, db, (kb > 0 || !zero) ? 1 : 0);
    asm volatile("wgmma.commit_group.sync.aligned;" ::: "memory");
    if (FIN || (TAILM & 2) || prevA) {
      asm volatile("wgmma.wait_group.sync.aligned 1;" ::: "memory");
      if (PROFML(OUTP) && elect && wg == 0) PROF3(64 + p.na);
      if (elect && prevA) { mbar_arrive(prevA); mbar_arrive_cluster(prevB, 0); mbar_arrive_cluster(prevB, 1); }
    }
    wg_mma<N>(acc, da + 2, db + 128, 1);
    wg_mma<N>(acc, da + 4, db + 256, 1);
    wg_mma<N>(acc, da + 6, db + 384, 1);
    asm volatile("wgmma.commit_group.sync.aligned;" ::: "memory");
    prevA = (kb < nblk - norel) ? bars + (BAR_AE + sa) * 8 : 0;
    prevB = bars + (EMPTY + p.sb) * 8;
    ++p.na;
    if (OUTP) {
      p.sb = (p.sb + 1) & 3;
      if (p.sb == 3) p.pb ^= 1;
    } else {
      if (++p.sb == 3) { p.sb = 0; p.pb ^= 1; }
    }
  }
  if (FIN) {
    asm volatile("wgmma.wait_group.sync.aligned 0;" ::: "memory");
    reg_fence(acc);
    if (elect && prevA) { mbar_arrive(prevA); mbar_arrive_cluster(prevB, 0); mbar_arrive_cluster(prevB, 1); }
  }
}

struct Role {
  int i, c, s, rank;
  int full0, part0;
};

__device__ __forceinline__ void softmax4(const float (&s0)[4], const float (&s1)[4], const float (&s2)[4], bool p0, bool p1, uint32_t msk,
                                         uint32_t& pa0, uint32_t& pa2, uint32_t& pa3, uint32_t& pb1) {
  constexpr float SC = 0.22360679774997896f * 1.4426950408889634f;
  const float l0 = p0 ? s1[0] : s0[0], l1 = p1 ? s1[1] : s0[1], h0 = p0 ? s2[2] : s1[2], h1 = p1 ? s2[3] : s1[3];
  float ml = fmaxf(l0, l1), mh = fmaxf(h0, h1);
  ml = fmaxf(ml, __shfl_xor_sync(0xffffffffu, ml, 1)); mh = fmaxf(mh, __shfl_xor_sync(0xffffffffu, mh, 1));
  ml = fmaxf(ml, __shfl_xor_sync(0xffffffffu, ml, 2)); mh = fmaxf(mh, __shfl_xor_sync(0xffffffffu, mh, 2));
  ml *= SC; mh *= SC;
  const uint32_t pl = pack_bf16(ex2(fmaf(l0, SC, -ml)), ex2(fmaf(l1, SC, -ml)));
  const uint32_t ph = pack_bf16(ex2(fmaf(h0, SC, -mh)), ex2(fmaf(h1, SC, -mh)));
  pa0 = pl & ~msk; pa2 = pl & msk; pa3 = ph & ~msk; pb1 = ph & msk;
}

__device__ __forceinline__ void attention(uint32_t stg, uint32_t gsm, int wg, int warp, int lane, bool first) {
  const int t = lane & 3, g = lane >> 2;
  const uint32_t qb = stg + (wg * 4 + warp) * 2560;
  const uint32_t kb = stg + STG_KV + wg * KPAR + warp * 256 + min(lane >> 3, 2) * 128 + (lane & 7) * 16;
  const bool p0 = 2 * t <= g, p1 = 2 * t + 1 <= g;
  const uint32_t msk = (p0 ? 0xffffu : 0u) | (p1 ? 0xffff0000u : 0u);
  const uint32_t mA = t < 2 ? 0xffffffffu : 0u;
  const float ninf = first ? -INFINITY : 0.f;
  const float ezl = lds32f(gsm + (2 * (warp * 16 + g) + wg) * 4), ezh = lds32f(gsm + (2 * (warp * 16 + g + 8) + wg) * 4);
  uint32_t q[5][4];
#pragma unroll
  for (int c = 0; c < 5; c++) ldsm_x4(qb + c * 512 + lane * 16, q[c]);
  __syncwarp();
  const uint32_t ob = qb + (lane & 15) * 160 + (lane >> 4) * 16;
  uint32_t ores[2][10];
#pragma unroll
  for (int hp = 0; hp < 2; hp++) {
#define QF(x, half) q[(5 * hp + (x)) >> 1][(((5 * hp + (x)) & 1) << 1) + (half)]
    uint32_t kf[5][4];
#pragma unroll
    for (int c = 0; c < 5; c++) ldsm_x4(kb + (5 * hp + c) * KC, kf[c]);
    float sa[3][4], sb[3][4];
#pragma unroll
    for (int j = 0; j < 3; j++) {
      sa[j][0] = sa[j][1] = sb[j][0] = sb[j][1] = (j == 0) ? ninf : 0.f;
      sa[j][2] = sa[j][3] = sb[j][2] = sb[j][3] = 0.f;
      mma16(sa[j], QF(0, 0), QF(0, 1), QF(1, 0), QF(1, 1), kf[0][j], kf[1][j]);
      mma16(sb[j], QF(3, 0), QF(3, 1), QF(4, 0), QF(4, 1), kf[3][j], kf[4][j]);
      mma8(sa[j], QF(2, 0) & mA, QF(2, 1) & mA, kf[2][j]);
      mma8(sb[j], QF(2, 0) & ~mA, QF(2, 1) & ~mA, kf[2][j]);
    }
    uint32_t vf[5][4];
#pragma unroll
    for (int c = 0; c < 5; c++) ldsm_x4_t(kb + (10 + 5 * hp + c) * KC, vf[c]);
    uint32_t a0, a2, a3, a1, b0, b2, b3, b1;
    softmax4(sa[0], sa[1], sa[2], p0, p1, msk, a0, a2, a3, a1);
    softmax4(sb[0], sb[1], sb[2], p0, p1, msk, b0, b2, b3, b1);
    constexpr uint32_t ONE = 0x3f803f80u;
    float o[6][4], su[2][4];
#pragma unroll
    for (int c = 0; c < 6; c++) o[c][0] = o[c][1] = o[c][2] = o[c][3] = 0.f;
#pragma unroll
    for (int c = 0; c < 2; c++) su[c][0] = su[c][1] = su[c][2] = su[c][3] = 0.f;
    mma16(su[0], a0, 0, a2, a3, ONE, ONE); mma16(su[1], b0, 0, b2, b3, ONE, ONE);
    mma8(su[0], 0, a1, ONE); mma8(su[1], 0, b1, ONE);
#pragma unroll
    for (int c = 0; c < 3; c++) {
      mma16(o[c], a0, 0, a2, a3, vf[c][0], vf[c][1]);
      mma16(o[3 + c], b0, 0, b2, b3, vf[2 + c][0], vf[2 + c][1]);
    }
#pragma unroll
    for (int c = 0; c < 3; c++) {
      mma8(o[c], 0, a1, vf[c][2]);
      mma8(o[3 + c], 0, b1, vf[2 + c][2]);
    }
    const float ral = ezl * rcp(su[0][0]), rah = ezh * rcp(su[0][2]), rbl = ezl * rcp(su[1][0]), rbh = ezh * rcp(su[1][2]);
    const float rml = t < 2 ? ral : rbl, rmh = t < 2 ? rah : rbh;
    ores[hp][0] = pack_bf16(o[0][0] * ral, o[0][1] * ral); ores[hp][1] = pack_bf16(o[0][2] * rah, o[0][3] * rah);
    ores[hp][2] = pack_bf16(o[1][0] * ral, o[1][1] * ral); ores[hp][3] = pack_bf16(o[1][2] * rah, o[1][3] * rah);
    ores[hp][4] = pack_bf16((t < 2 ? o[2][0] : o[3][0]) * rml, (t < 2 ? o[2][1] : o[3][1]) * rml);
    ores[hp][5] = pack_bf16((t < 2 ? o[2][2] : o[3][2]) * rmh, (t < 2 ? o[2][3] : o[3][3]) * rmh);
    ores[hp][6] = pack_bf16(o[4][0] * rbl, o[4][1] * rbl); ores[hp][7] = pack_bf16(o[4][2] * rbh, o[4][3] * rbh);
    ores[hp][8] = pack_bf16(o[5][0] * rbl, o[5][1] * rbl); ores[hp][9] = pack_bf16(o[5][2] * rbh, o[5][3] * rbh);
#undef QF
  }
  stsm_x4(ob, ores[0][0], ores[0][1], ores[0][2], ores[0][3]);
  stsm_x4(ob + 32, ores[0][4], ores[0][5], ores[0][6], ores[0][7]);
  stsm_x4(ob + 64, ores[0][8], ores[0][9], ores[1][0], ores[1][1]);
  stsm_x4(ob + 96, ores[1][2], ores[1][3], ores[1][4], ores[1][5]);
  stsm_x4(ob + 128, ores[1][6], ores[1][7], ores[1][8], ores[1][9]);
}

__device__ __forceinline__ void consumer(uint32_t sbase, int wg, const Role& R, const Maps& maps, const uint32_t (&bv)[28]) {
  int tid = threadIdx.x & 127;
  const bool elect = (tid == 0);
  const uint32_t bars = sbase + OFF_BAR;
  Pipe p{0, 0, 0};
#define LANE_VARS                                                                                     \
  tid = opaque(tid);                                                                                  \
  const int warp = tid >> 5, lane = tid & 31, t = lane & 3, g = lane >> 2;                            \
  const int r16 = ((lane >> 3) & 1) * 8 + (lane & 7);                                                 \
  const int srow = wg * 64 + warp * 16 + r16;                                                         \
  const int hi = lane >> 4;                                                                           \
  (void)t; (void)g; (void)srow; (void)hi;
  {
    float acc[112];
    const int nch = R.s ? 26 : 28;
    cluster_wait();
#pragma unroll
    for (int c = 0; c < 28; c++) {
      acc[4 * c] = bf_lo(bv[c]); acc[4 * c + 1] = bf_hi(bv[c]); acc[4 * c + 2] = bf_lo(bv[c]); acc[4 * c + 3] = bf_hi(bv[c]);
    }
    if (tid == 0 && wg == 0) PROF(1);
    if (R.s == 0) mainloop<224, 112, false, true>(acc, 10, p, sbase, wg, elect, false, 0, -1);
    else mainloop<208, 112, false, true>(acc, 10, p, sbase, wg, elect, false, 0, -1);
    if (tid == 0) PROF3(wg ? 40 : 41); if (tid == 0 && wg == 0) PROF(2);
    LANE_VARS
    mbar_wait(bars + BAR_RQ * 8, 0);
    const uint32_t sa = sbase + OFF_STG + srow * 128;
    const int sw = srow & 7;
    auto act2 = [&](float a, float b) { uint32_t r = pack_bf16_relu(a, b); return mul_bf16x2(r, r); };
#pragma unroll
    for (int c = 0; c < 28; c += 2) {
      if (c < 26 || c < nch)
        stsm_x4(sa + (c >> 3) * 16384 + ((((c & 7) + hi) ^ sw) << 4), act2(acc[4 * c], acc[4 * c + 1]), act2(acc[4 * c + 2], acc[4 * c + 3]),
                act2(acc[4 * c + 4], acc[4 * c + 5]), act2(acc[4 * c + 6], acc[4 * c + 7]));
    }
    fence_async_smem();
    __syncwarp();
    if (lane == 0) mbar_arrive(bars + BAR_S1F * 8);
    if (tid == 0) PROF3(wg ? 42 : 43); if (tid == 0 && wg == 0) PROF(3);
  }
  {
    float acc[124];
    mainloop<248, 124, false, true>(acc, 10, p, sbase, wg, elect, true, 0, -1);
    if (tid == 0) PROF3(wg ? 44 : 45); if (tid == 0 && wg == 0) PROF(4);
    LANE_VARS
    if (t == 0) {
      const uint32_t ga = sbase + OFF_G + (2 * (warp * 16 + g) + wg) * 4;
      sts32f(ga, __expf(fminf(fmaxf(acc[120], -60.f), 60.f)));
      sts32f(ga + 64, __expf(fminf(fmaxf(acc[122], -60.f), 60.f)));
    }
    mbar_wait(bars + BAR_S1E * 8, 0);
    const uint32_t sq = sbase + OFF_STG + (wg * 4 + warp) * 2560 + lane * 16;
    const uint32_t sk = sbase + OFF_STG + STG_KV + wg * KPAR + (warp * 16 + 8 + r16) * 16 + hi * KC;
#pragma unroll
    for (int c = 0; c < 30; c += 2) {
      const uint32_t a = (c < 10) ? sq + c * 256 : sk + (c - 10) * KC;
      stsm_x4(a, pack_bf16(acc[4 * c], acc[4 * c + 1]), pack_bf16(acc[4 * c + 2], acc[4 * c + 3]),
              pack_bf16(acc[4 * c + 4], acc[4 * c + 5]), pack_bf16(acc[4 * c + 6], acc[4 * c + 7]));
    }
    __syncwarp();
    if (lane == 0) mbar_arrive(bars + BAR_S2F * 8);
    if (tid == 0) PROF3(wg ? 46 : 47); if (tid == 0 && wg == 0) PROF(5);
  }
  {
    float acc[80];
    const int nblk = (R.s ? 19 : 18) - NPRE;
    const bool home = (wg == R.s);
    p.sb = 3; p.pb = 0;
    if (!home) {
      const uint32_t b2a = sbase + OFF_B2 + (opaque(tid) & 3) * 4;
#pragma unroll
      for (int c = 0; c < 20; c++) {
        const uint32_t v = lds32(b2a + c * 16);
        acc[4 * c] = bf_lo(v); acc[4 * c + 1] = bf_hi(v); acc[4 * c + 2] = bf_lo(v); acc[4 * c + 3] = bf_hi(v);
      }
    }
    mainloop<160, 80, true, true>(acc, NPRE, p, sbase, wg, elect, home, 0, -1);
    {
      LANE_VARS
      if (tid == 0) PROF3(wg ? 48 : 49); if (tid == 0 && wg == 0) PROF(17);
      mbar_wait(bars + BAR_HALO * 8, 0);
      if (tid == 0 && wg == 0) PROF(22);
      attention(sbase + OFF_STG, sbase + OFF_G, wg, warp, lane, R.i == 0 && warp == 0);
      fence_async_smem();
      __syncwarp();
      if (lane == 0) mbar_arrive(bars + BAR_OF * 8);
      if (tid == 0) PROF3(wg ? 50 : 51); if (tid == 0 && wg == 0) PROF(18);
    }
    mainloop<160, 80, true, false>(acc, nblk, p, sbase, wg, elect, false, 4, (home && LAG > 0) ? nblk - LAG : -1);
    LANE_VARS
    const int row_lo = wg * 64 + warp * 16 + g;
    const float glo = rcp(1.f + lds32f(sbase + OFF_G + row_lo * 4)), ghi = rcp(1.f + lds32f(sbase + OFF_G + (row_lo + 8) * 4));
    const int lrow = warp * 16 + r16;
    const uint32_t so = sbase + OFF_STG + wg * 24576 + lrow * 128;
    const int sw = lrow & 7;
    mbar_wait(bars + BAR_S2E * 8, 0);
    asm volatile("wgmma.wait_group.sync.aligned 0;" ::: "memory");
    if (!home && LAG > 0) bar_arrive(3, 256);
    reg_fence(acc);
    if (tid == 0) PROF(home ? 6 : 9);
#pragma unroll
    for (int q = 0; q < 10; q++)
      stsm_x4(so + (q >> 2) * 8192 + (((((2 * q) & 7) + hi) ^ sw) << 4),
              pack_bf16(acc[8 * q] * glo, acc[8 * q + 1] * glo), pack_bf16(acc[8 * q + 2] * ghi, acc[8 * q + 3] * ghi),
              pack_bf16(acc[8 * q + 4] * glo, acc[8 * q + 5] * glo), pack_bf16(acc[8 * q + 6] * ghi, acc[8 * q + 7] * ghi));
    if (tid == 0 && home) PROF3(110);
    fence_async_smem();
    __syncwarp();
    if (tid == 0) PROF3(home ? 111 : 109);
    if (elect_one()) {
      const bool odd = R.c & 1;
      const int x0 = R.c * 160 + (odd ? 32 : 0), x2 = R.c * 160 + (odd ? 0 : 128), y = R.i * 128 + wg * 64 + warp * 16;
      const uint32_t src = sbase + OFF_STG + wg * 24576 + warp * 2048;
      tma2d_reduce(&maps.of, src, x0, y);
      tma2d_reduce(&maps.of, src + 8192, x0 + 64, y);
      tma2d_reduce(&maps.on, src + 16384, x2, y);
      bulk_commit();
      if (home && warp == 0) asm volatile("red.relaxed.gpu.global.add.u32 [%0], 1;" ::"l"(&g_done[0]) : "memory");
      if (tid == 0 && home) PROF3(112);
      bulk_wait_read();
      if (tid == 0 && !home) PROF3(114);
    }
    __syncwarp();
    if (tid == 0 && home) {
      PROF(8);
    }
  }
}

__device__ __forceinline__ void producer(uint32_t sbase, const Maps& maps, const Role& R,
                                         const __nv_bfloat16* w2, const __nv_bfloat16* wo) {
  const uint32_t bars = sbase + OFF_BAR;
  uint32_t na = 3, s = 0, ph = 0;
  const int jq = R.c * 2 + R.s, y0 = R.i * 128;
  {
    const CUtensorMap* ta = &maps.ax[0];
    const CUtensorMap* t0 = &maps.w1f;
    const CUtensorMap* t1 = R.rank ? &maps.w1n[R.s] : &maps.w1f;
    int x0 = R.full0 + R.rank * 64, x1 = R.rank ? R.part0 : R.full0 + 128, y = 192, xa = 192, ya = y0;
    uint32_t bytes = R.s ? 26624 : 28672;
    const uint32_t db = sbase + OFF_B + R.rank * 8192;
#pragma unroll 1
    for (int m = 3; m < 6; m++) {
      if (m == jq) pf3d(ta, m * 64, ya);
      if (m == (R.i >> 1)) { pf2d(t0, x0, m * 64); pf2d(t1, x1, m * 64); }
    }
#pragma unroll 1
    for (int n = 3; n < 20; ++n) {
      if (n == 10) {
        PROF(14); mbar_wait(bars + BAR_RQ * 8, 0); PROF(15);
        ta = &maps.ax[1]; t0 = t1 = &maps.wq;
        x0 = R.rank * 64; x1 = x0 + 128; y = jq * DM; xa = 0; ya = R.i * 64; bytes = 32768;
      }
      const uint32_t sa = na & 3;
      mbar_wait(bars + (BAR_AE + sa) * 8, ((na >> 2) & 1) ^ 1);
      mbar_expect_tx(bars + (BAR_AF + sa) * 8, 16384);
      tma3d(sbase + OFF_A + sa * 16384, ta, bars + (BAR_AF + sa) * 8, xa, ya);
      ++na;
      mbar_wait(bars + (BAR_BE + s) * 8, ph);
      const uint32_t fb = bars + (BAR_BF + s) * 8;
      mbar_expect_tx(fb, bytes);
      tma2d_mc(db + s * 32768, t0, fb, x0, y);
      tma2d_mc(db + s * 32768 + 16384, t1, fb, x1, y);
      PROF2(64 + na - 1);
      if (n < PFN) {
        if (((n + 3) & 7) == jq) pf3d(ta, xa + 192, ya);
        if (((n + 3) & 7) == (R.i >> 1)) { pf2d(t0, x0, y + 192); pf2d(t1, x1, y + 192); }
      }
      if (n == 6) {
        prefetch_l2(reinterpret_cast<const uint8_t*>(w2) + blockIdx.x * 17280, 17280);
        prefetch_l2(reinterpret_cast<const uint8_t*>(wo) + blockIdx.x * 6400, 6400);
      }
      if (++s == 3) { s = 0; ph ^= 1; }
      xa += 64; y += 64;
    }
  }
  {
    const bool odd = R.c & 1;
    const int x0 = R.c * 160 + (odd ? 32 : 0), x2 = R.c * 160 + (odd ? 0 : 128);
    const CUtensorMap* tf = &maps.w2f;
    const CUtensorMap* tp = &maps.w2n;
    const int nh = R.s ? 14 : 13;
    int y = R.s ? 13 * 64 : 0, xa = DM + y;
    const uint32_t db = sbase + OFF_B + R.rank * 4096;
#pragma unroll 1
    for (int n = 0; n < nh + 5; ++n) {
      if (n == 0) { PROF(10); mbar_wait(bars + BAR_RH * 8, 0); PROF(11); }
      if (n == nh) {
        PROF(12); mbar_wait(bars + BAR_RO * 8, 0); PROF(13);
        tf = &maps.wof; tp = &maps.won;
        y = R.s * 320; xa = y;
      }
      const uint32_t sa = na & 3;
      mbar_wait(bars + (BAR_AE + sa) * 8, ((na >> 2) & 1) ^ 1);
      mbar_expect_tx(bars + (BAR_AF + sa) * 8, 16384);
      tma2d(sbase + OFF_A + sa * 16384, &maps.hf, bars + (BAR_AF + sa) * 8, xa, y0);
      ++na;
      const uint32_t sl = (n + 3) & 3;
      if (n < 3) {
        mbar_wait(bars + (BAR_BE + s) * 8, ph);
        if (++s == 3) { s = 0; ph ^= 1; }
      } else if (n >= 4) {
        mbar_wait(bars + (BAR_CE + sl) * 8, ((n >> 2) & 1) ^ 1);
      }
      const uint32_t fb = bars + (BAR_CF + sl) * 8;
      mbar_expect_tx(fb, 20480);
      const uint32_t d = db + sl * 24576;
      const int yy = y + R.rank * 32;
      tma2d_mc(d, tf, fb, x0, yy);
      tma2d_mc(d + 8192, tf, fb, x0 + 64, yy);
      tma2d_mc(d + 16384, tp, fb, x2, yy);
      PROF2(64 + na - 1);
      xa += 64; y += 64;
    }
  }
}

__device__ __forceinline__ void repack(uint32_t sbase, const Role& R, int half, const __nv_bfloat16* __restrict__ wqkv, const __nv_bfloat16* __restrict__ gate_w) {
  const int lane = threadIdx.x & 31;
  const int jq = R.c * 2 + R.s, r0 = R.i * 40 + half * 20;
  const int part = lane / 10;
  const uint8_t* src = reinterpret_cast<const uint8_t*>(wqkv + (size_t)r0 * (3 * DM) + part * DM + jq * 80 + (lane - part * 10) * 8);
  const uint32_t stg = sbase + OFF_STG + half * 10240;
  uint32_t gv = 0;
  if (lane < 20) gv = __ldg(reinterpret_cast<const unsigned short*>(gate_w + r0) + lane);
  if (lane < 30) {
#pragma unroll
    for (int k = 0; k < 20; k++)
      asm volatile("cp.async.cg.shared.global [%0], [%1], 16;" ::"r"(stg + k * 512 + lane * 16), "l"(src + k * (3 * DM * 2)) : "memory");
  }
  if (lane < 20) { sts128(stg + lane * 512 + 480, make_uint4(gv, 0, 0, 0)); sts128(stg + lane * 512 + 496, make_uint4(0, 0, 0, 0)); }
  asm volatile("cp.async.wait_all;" ::: "memory");
  if (half == 0 && lane == 0) PROF(26);
  fence_async_smem();
  __syncwarp();
  if (elect_one()) {
    asm volatile("cp.async.bulk.global.shared::cta.bulk_group [%0], [%1], %2;" ::"l"(g_wqkv + (size_t)(jq * DM + r0) * 256), "r"(stg), "r"(10240) : "memory");
    bulk_commit();
    bulk_wait();
    if (half == 0) PROF(31);
    fence_async();
    red_release(g_rep + jq * 32, 1);
    if (half == 0) PROF(21);
  }
  __syncwarp();
}

__device__ __forceinline__ void aux(uint32_t sbase, const Maps& maps, const Role& R, const __nv_bfloat16* __restrict__ b2, __nv_bfloat16* __restrict__ out) {
  const int lane = threadIdx.x & 31;
  const uint32_t bars = sbase + OFF_BAR;
  const uint32_t stg = sbase + OFF_STG;
  const int i = R.i, jq = R.c * 2 + R.s;
  unsigned* fl = g_flags + i * 32;
  const unsigned epoch = ld_relaxed(&g_done[0]) >> 7;
#pragma unroll
  for (int k = 0; k < 3; k++) {
    const int n = (k * 32 + lane) * 2;
    if (n < 160) {
      const int col = R.c * 160 + ((R.c & 1) ? (n < 128 ? n + 32 : n - 128) : n);
      sts32(sbase + OFF_B2 + n * 2, __ldg(reinterpret_cast<const uint32_t*>(b2 + col)));
    }
  }
  cluster_wait();
  __syncwarp();
  if (elect_one()) {
    wait_flag(g_rep + jq * 32, (epoch + 1) * 32);
    fence_async();
    mbar_arrive(bars + BAR_RQ * 8);
    PROF(20);
  }
  __syncwarp();
  if (lane < 20) {
    uint4* d = reinterpret_cast<uint4*>(out + (size_t)(i * 128 + R.s * 64) * DM + R.c * 160) + lane;
#pragma unroll 8
    for (int r = 0; r < 64; r++) d[r * (DM / 8)] = make_uint4(0, 0, 0, 0);
  }
  __syncwarp();
  if (elect_one()) {
    mbar_wait(bars + BAR_S1F * 8, 0);
#pragma unroll 1
    for (int k = 0; k < 7; k++) {
      if (k < 6) tma2d_store(&maps.hs, stg + k * 8192, DM + R.full0 + (k >> 1) * 64, i * 128 + (k & 1) * 64);
      else tma2d_store(&maps.hn[R.s], stg + 49152, DM + R.part0, i * 128);
      bulk_commit();
      if (k < 6) __nanosleep(HPACE);
    }
    bulk_wait_read();
    mbar_arrive(bars + BAR_S1E * 8);
    bulk_wait();
    fence_async();
    red_release(fl + FL_H, 1);
    PROF(16);
    wait_flag(fl + FL_H, (epoch + 1) * 8);
    fence_async();
    mbar_arrive(bars + BAR_RH * 8);
  }
  __syncwarp();
  mbar_wait(bars + BAR_S2F * 8, 0);
  {
    const uint32_t hs = stg + STG_KV + (lane >> 3) * KC + (lane & 7) * 16;
    if (i < 15) {
      uint4* d = &g_halo[(i * 8 + jq) * 320 + lane];
#pragma unroll
      for (int k = 0; k < 10; k++) {
        const uint4 v = lds128(hs + k * 4 * KC + 1024);
        st_relaxed4(d + k * 32, make_uint4(max(v.x, 1u), max(v.y, 1u), max(v.z, 1u), max(v.w, 1u)));
      }
    }
    uint4 v[10];
#pragma unroll
    for (int k = 0; k < 10; k++) v[k] = make_uint4(0, 0, 0, 0);
    if (i > 0) {
      uint4* src = &g_halo[((i - 1) * 8 + jq) * 320 + lane];
      int iter = 0;
      bool ok;
      do {
        ok = true;
#pragma unroll
        for (int k = 0; k < 10; k++) {
          v[k] = ld_relaxed4(src + k * 32);
          ok = ok && v[k].x && v[k].y && v[k].z && v[k].w;
        }
        if (++iter > (1 << 22)) asm volatile("trap;");
      } while (!ok);
#pragma unroll
      for (int k = 0; k < 10; k++) st_relaxed4(src + k * 32, make_uint4(0, 0, 0, 0));
    }
#pragma unroll
    for (int k = 0; k < 10; k++) sts128(hs + k * 4 * KC, v[k]);
  }
  __syncwarp();
  if (elect_one()) {
    mbar_arrive(bars + BAR_HALO * 8);
    mbar_wait(bars + BAR_OF * 8, 0);
    tma3d_store(&maps.os, stg, jq * 80, i * 64);
    bulk_commit();
    bulk_wait_read();
    mbar_arrive(bars + BAR_S2E * 8);
    bulk_wait();
    fence_async();
    red_release(fl + FL_O, 1);
    PROF(19);
    wait_flag(fl + FL_O, (epoch + 1) * 8);
    fence_async();
    mbar_arrive(bars + BAR_RO * 8);
  }
}

__global__ void __launch_bounds__(384, 1)
fused_kernel(const __nv_bfloat16* __restrict__ wqkv, const __nv_bfloat16* __restrict__ b1, const __nv_bfloat16* __restrict__ w2,
             const __nv_bfloat16* __restrict__ wo, const __nv_bfloat16* __restrict__ b2, const __nv_bfloat16* __restrict__ gate_w,
             __nv_bfloat16* __restrict__ out, const __grid_constant__ Maps maps) {
  extern __shared__ __align__(1024) uint8_t smem_raw[];
  const uint32_t sbase = smem_u32(smem_raw);
  uint32_t rank;
  asm volatile("mov.u32 %0, %%cluster_ctarank;" : "=r"(rank));
  Role R;
  {
    const int q = blockIdx.x >> 1;
    int grp, m;
    if (q < 4) { grp = 0; m = q; }
    else if (q < 36) { grp = 1 + ((q - 4) & 7); m = (q - 4) >> 3; }
    else { grp = 9 + (q - 36) % 7; m = (q - 36) / 7; }
    R.i = (grp >> 1) * 2 + (int)rank; R.s = grp & 1; R.c = m; R.rank = (int)rank;
    R.full0 = 192 * (2 * m + R.s);
    R.part0 = R.s ? 1664 + 16 * m : 1536 + 32 * m;
  }
  const int wid = __shfl_sync(0xffffffffu, (int)(threadIdx.x >> 5), 0);
  const uint32_t bars = sbase + OFF_BAR;
  if (wid >= 8) {
    if (wid == 8) {
      if (elect_one()) {
        PROF(0);
#pragma unroll
        for (int b = 0; b < 4; b++) mbar_init(bars + (BAR_AF + b) * 8, 1);
#pragma unroll
        for (int b = 0; b < 3; b++) mbar_init(bars + (BAR_BF + b) * 8, 1);
        asm volatile("fence.mbarrier_init.release.cluster;" ::: "memory");
      }
    } else if (wid == 9) {
      if (elect_one()) {
#pragma unroll
        for (int b = 0; b < NBARS; b++)
          if ((b >= BAR_AE && b < BAR_BF) || b >= BAR_BE) mbar_init(bars + b * 8, 1u << ((BAR_COUNTS >> (2 * b)) & 3));
        asm volatile("fence.mbarrier_init.release.cluster;" ::: "memory");
      }
    } else {
      if (elect_one()) {
        if (wid == 10) { prefetch_tm(&maps.w1f); prefetch_tm(&maps.w1n[R.s]); } else prefetch_tm(&maps.ax[0]);
      }
    }
    __syncwarp();
    cluster_arrive();
    asm volatile("setmaxnreg.dec.sync.aligned.u32 88;");
    if (wid == 8) {
      if (elect_one()) {
        PROF(23);
        const uint32_t bytes = R.s ? 26624 : 28672;
#pragma unroll
        for (int n = 0; n < 3; n++) {
          const uint32_t fb = bars + (BAR_BF + n) * 8, db = sbase + OFF_B + n * 32768;
          mbar_expect_tx(bars + (BAR_AF + n) * 8, 16384);
          tma3d(sbase + OFF_A + n * 16384, &maps.ax[0], bars + (BAR_AF + n) * 8, n * 64, R.i * 128);
          mbar_expect_tx(fb, bytes);
          tma2d(db, &maps.w1f, fb, R.full0, n * 64);
          tma2d(db + 8192, &maps.w1f, fb, R.full0 + 64, n * 64);
          tma2d(db + 16384, &maps.w1f, fb, R.full0 + 128, n * 64);
          tma2d(db + 24576, &maps.w1n[R.s], fb, R.part0, n * 64);
          if (n == 0) PROF(24);
        }
        PROF(30);
        if (sbase & 1023) asm volatile("trap;");
      }
      __syncwarp();
      cluster_wait();
      if (elect_one()) { PROF(25); producer(sbase, maps, R, w2, wo); }
    } else if (wid == 9) {
      aux(sbase, maps, R, b2, out);
    } else {
      repack(sbase, R, wid - 10, wqkv, gate_w);
      if (elect_one()) {
#pragma unroll 1
        for (int k = wid - 10; k < NMAPS; k += 2) prefetch_tm(&maps.ax[0] + k);
      }
      __syncwarp();
      cluster_wait();
    }
  } else {
    uint32_t bv[28];
    {
      const int nch = R.s ? 26 : 28;
      const uint32_t* bp = reinterpret_cast<const uint32_t*>(b1 + R.full0) + (threadIdx.x & 3);
      const uint32_t* bq = reinterpret_cast<const uint32_t*>(b1 + R.part0) + (threadIdx.x & 3);
#pragma unroll
      for (int c = 0; c < 28; c++) {
        bv[c] = 0;
        if (c < 24) bv[c] = __ldg(bp + c * 4);
        else if (c < nch) bv[c] = __ldg(bq + (c - 24) * 4);
      }
    }
    cluster_arrive();
    if (threadIdx.x == 0) PROF(27);
    asm volatile("setmaxnreg.inc.sync.aligned.u32 208;");
    if (threadIdx.x == 0) PROF(28);
    consumer(sbase, wid >> 2, R, maps, bv);
  }
}

typedef CUresult (*EncFn)(CUtensorMap*, CUtensorMapDataType, cuuint32_t, void*, const cuuint64_t*, const cuuint64_t*, const cuuint32_t*,
                          const cuuint32_t*, CUtensorMapInterleave, CUtensorMapSwizzle, CUtensorMapL2promotion, CUtensorMapFloatOOBfill);

void make_map(EncFn enc, CUtensorMap* m, const void* base, uint64_t d0, uint64_t d1, uint64_t pitch1, uint32_t b0, uint32_t b1,
              bool swz = true, uint64_t d2 = 0, uint64_t pitch2 = 0, uint32_t b2 = 1) {
  cuuint64_t dims[3] = {d0, d1, d2};
  cuuint64_t strides[2] = {pitch1, pitch2};
  cuuint32_t box[3] = {b0, b1, b2};
  cuuint32_t es[3] = {1, 1, 1};
  CUresult res = enc(m, CU_TENSOR_MAP_DATA_TYPE_BFLOAT16, d2 ? 3 : 2, const_cast<void*>(base), dims, strides, box, es,
                     CU_TENSOR_MAP_INTERLEAVE_NONE, swz ? CU_TENSOR_MAP_SWIZZLE_128B : CU_TENSOR_MAP_SWIZZLE_NONE,
                     CU_TENSOR_MAP_L2_PROMOTION_L2_128B, CU_TENSOR_MAP_FLOAT_OOB_FILL_NONE);
  (void)res;
}

}

extern "C" void kernel_launch(void* const* d_in, const int* in_sizes, int n_in, void* d_out, int out_size) {
  (void)in_sizes; (void)n_in; (void)out_size;
  const __nv_bfloat16* x = (const __nv_bfloat16*)d_in[0];
  const __nv_bfloat16* wqkv = (const __nv_bfloat16*)d_in[1];
  const __nv_bfloat16* wo = (const __nv_bfloat16*)d_in[2];
  const __nv_bfloat16* w1 = (const __nv_bfloat16*)d_in[4];
  const __nv_bfloat16* b1 = (const __nv_bfloat16*)d_in[5];
  const __nv_bfloat16* w2 = (const __nv_bfloat16*)d_in[6];
  const __nv_bfloat16* b2 = (const __nv_bfloat16*)d_in[7];
  const __nv_bfloat16* gate_w = (const __nv_bfloat16*)d_in[8];

  static EncFn enc = nullptr;
  static void* act_ptr = nullptr;
  static void* wq_ptr = nullptr;
  if (!enc) {
    void* fn = nullptr;
    cudaDriverEntryPointQueryResult qr;
    cudaGetDriverEntryPoint("cuTensorMapEncodeTiled", &fn, cudaEnableDefault, &qr);
    enc = (EncFn)fn;
    cudaGetSymbolAddress(&act_ptr, g_act);
    cudaGetSymbolAddress(&wq_ptr, g_wqkv);
    cudaFuncSetAttribute(fused_kernel, cudaFuncAttributeMaxDynamicSharedMemorySize, SMEM_LAUNCH);
  }
  Maps maps;
  make_map(enc, &maps.ax[0], x, DM, SEQ, DM * 2, 64, 128, true, 1, (uint64_t)SEQ * DM * 2, 1);
  make_map(enc, &maps.ax[1], x, DM, SEQ / 2, DM * 4, 64, 64, true, 2, DM * 2, 2);
  make_map(enc, &maps.w1f, w1, FF, DM, FF * 2, 64, 64);
  make_map(enc, &maps.w1n[0], w1, FF, DM, FF * 2, 32, 64);
  make_map(enc, &maps.w1n[1], w1, FF, DM, FF * 2, 16, 64);
  make_map(enc, &maps.wq, wq_ptr, 256, 8 * DM, 512, 64, 64);
  make_map(enc, &maps.hs, act_ptr, ACT_LD, SEQ, ACT_LD * 2, 64, 64);
  make_map(enc, &maps.hn[0], act_ptr, ACT_LD, SEQ, ACT_LD * 2, 32, 128);
  make_map(enc, &maps.hn[1], act_ptr, ACT_LD, SEQ, ACT_LD * 2, 16, 128);
  make_map(enc, &maps.os, act_ptr, ACT_LD, SEQ / 2, ACT_LD * 4, 80, 64, false, 2, ACT_LD * 2, 2);
  make_map(enc, &maps.hf, act_ptr, ACT_LD, SEQ, ACT_LD * 2, 64, 128);
  make_map(enc, &maps.w2f, w2, DM, FF, DM * 2, 64, 32);
  make_map(enc, &maps.w2n, w2, DM, FF, DM * 2, 32, 32);
  make_map(enc, &maps.wof, wo, DM, DM, DM * 2, 64, 32);
  make_map(enc, &maps.won, wo, DM, DM, DM * 2, 32, 32);
  make_map(enc, &maps.of, d_out, DM, SEQ, DM * 2, 64, 16);
  make_map(enc, &maps.on, d_out, DM, SEQ, DM * 2, 32, 16);

  cudaLaunchConfig_t cfg = {};
  cfg.gridDim = dim3(128);
  cfg.blockDim = dim3(384);
  cfg.dynamicSmemBytes = SMEM_LAUNCH;
  cfg.stream = cudaStreamPerThread;
  cudaLaunchAttribute attr[1];
  attr[0].id = cudaLaunchAttributeClusterDimension;
  attr[0].val.clusterDim.x = 2; attr[0].val.clusterDim.y = 1; attr[0].val.clusterDim.z = 1;
  cfg.attrs = attr; cfg.numAttrs = 1;
  cudaLaunchKernelEx(&cfg, fused_kernel, wqkv, b1, w2, wo, b2, gate_w, (__nv_bfloat16*)d_out, maps);
}
```

```cpp
#include <cuda_runtime.h>
#include <cuda_bf16.h>
#include <cuda.h>
#include <stdint.h>

namespace {

constexpr int SEQ = 2048, DM = 640, FF = 1728;
constexpr int ACT_LD = DM + FF;
constexpr int OFF_A = 0;
constexpr int OFF_B = 65536;
constexpr int OFF_STG = 163840;
constexpr int STG_KV = 20480, KC = 1152, KPAR = 20 * KC;
constexpr int STG_BYTES = STG_KV + 2 * KPAR;
constexpr int OFF_BAR = OFF_STG + STG_BYTES;
constexpr int OFF_G = OFF_BAR + 256;
constexpr int OFF_B2 = OFF_G + 512;
constexpr int SMEM_TOTAL = OFF_B2 + 320;
static_assert(SMEM_TOTAL <= 232448, "smem");

constexpr int NPRE = 4;
constexpr int HPACE = 350;
constexpr int NP0 = 2;
constexpr int NA0 = 3;
constexpr int PFI = 3;
constexpr int PFD = 3;
constexpr int PFW = 7;

constexpr int BAR_AF = 0, BAR_AE = 4, BAR_BF = 8, BAR_BE = 12, BAR_S1F = 16, BAR_S1E = 17, BAR_S2F = 18,
              BAR_HALO = 19, BAR_OF = 20, BAR_S2E = 21, BAR_RQ = 22, BAR_RH = 23, BAR_RO = 24, NBARS = 25;
constexpr uint32_t B3_OFF = OFF_STG + 20480 - OFF_B;

constexpr unsigned long long bar_counts() {
  unsigned long long k = 0;
  for (int b = 0; b < 32; b++) {
    const int e = (b >= BAR_AE && b < BAR_BF) ? 1 : (b >= BAR_BE && b < BAR_S1F) ? 2
                  : (b == BAR_S1F || b == BAR_S2F || b == BAR_OF) ? 3 : 0;
    k |= (unsigned long long)e << (2 * b);
  }
  return k;
}
constexpr unsigned long long BAR_COUNTS = bar_counts();

constexpr int FL_H = 0, FL_O = 1;

struct Maps {
  CUtensorMap ax;
  CUtensorMap w1f, w1n[2];
  CUtensorMap wq;
  CUtensorMap hs, hn[2];
  CUtensorMap os;
  CUtensorMap hf;
  CUtensorMap w2f, w2n, wof, won;
  CUtensorMap of, on;
};
constexpr int NMAPS = sizeof(Maps) / sizeof(CUtensorMap);

__device__ __nv_bfloat16 g_act[SEQ * ACT_LD];
__device__ __nv_bfloat16 g_wqkv[8 * DM * 256];
__device__ uint4 g_halo[16 * 8 * 320];
__device__ unsigned g_flags[16 * 32];
__device__ unsigned g_rep[8 * 32];

__device__ __forceinline__ uint32_t smem_u32(const void* p) { return (uint32_t)__cvta_generic_to_shared(p); }
__device__ __forceinline__ void mbar_init(uint32_t bar, uint32_t cnt) { asm volatile("mbarrier.init.shared::cta.b64 [%0], %1;" ::"r"(bar), "r"(cnt) : "memory"); }
__device__ __forceinline__ void mbar_expect_tx(uint32_t bar, uint32_t bytes) { asm volatile("mbarrier.arrive.expect_tx.shared::cta.b64 _, [%0], %1;" ::"r"(bar), "r"(bytes) : "memory"); }
__device__ __forceinline__ void mbar_wait(uint32_t bar, uint32_t parity) {
  asm volatile(
      "{\n.reg .pred p;\n.reg .u32 c;\nmov.u32 c, 0;\n"
      "LAB_WAIT:\n"
      "mbarrier.try_wait.parity.shared::cta.b64 p, [%0], %1;\n"
      "@p bra DONE;\n"
      "add.u32 c, c, 1;\n"
      "setp.lt.u32 p, c, 0x4000000;\n"
      "@p bra LAB_WAIT;\n"
      "trap;\n"
      "DONE:\n}" ::"r"(bar), "r"(parity) : "memory");
}
__device__ __forceinline__ void mbar_arrive(uint32_t bar) { asm volatile("mbarrier.arrive.shared::cta.b64 _, [%0];" ::"r"(bar) : "memory"); }
__device__ __forceinline__ void mbar_arrive_cluster(uint32_t bar, uint32_t cta) {
  asm volatile("{\n.reg .b32 ra;\nmapa.shared::cluster.u32 ra, %0, %1;\nmbarrier.arrive.shared::cluster.b64 _, [ra];\n}" ::"r"(bar), "r"(cta) : "memory");
}
__device__ __forceinline__ void tma2d(uint32_t dst, const CUtensorMap* tm, uint32_t bar, int c0, int c1) {
  asm volatile("cp.async.bulk.tensor.2d.shared::cluster.global.mbarrier::complete_tx::bytes [%0], [%1, {%3, %4}], [%2];"
               ::"r"(dst), "l"(tm), "r"(bar), "r"(c0), "r"(c1) : "memory");
}
__device__ __forceinline__ void tma3d(uint32_t dst, const CUtensorMap* tm, uint32_t bar, int c0, int c1) {
  asm volatile("cp.async.bulk.tensor.3d.shared::cluster.global.mbarrier::complete_tx::bytes [%0], [%1, {%3, %4, %5}], [%2];"
               ::"r"(dst), "l"(tm), "r"(bar), "r"(c0), "r"(c1), "r"(0) : "memory");
}
__device__ __forceinline__ void tma2d_mc(uint32_t dst, const CUtensorMap* tm, uint32_t bar, int c0, int c1) {
  asm volatile("cp.async.bulk.tensor.2d.shared::cluster.global.mbarrier::complete_tx::bytes.multicast::cluster [%0], [%1, {%3, %4}], [%2], %5;"
               ::"r"(dst), "l"(tm), "r"(bar), "r"(c0), "r"(c1), "h"((uint16_t)3) : "memory");
}
__device__ __forceinline__ void tma2d_reduce(const CUtensorMap* tm, uint32_t src, int c0, int c1) {
  asm volatile("cp.reduce.async.bulk.tensor.2d.global.shared::cta.add.tile.bulk_group [%0, {%2, %3}], [%1];" ::"l"(tm), "r"(src), "r"(c0), "r"(c1) : "memory");
}
__device__ __forceinline__ void tma3d_store(const CUtensorMap* tm, uint32_t src, int c0, int c1, int c2 = 0) {
  asm volatile("cp.async.bulk.tensor.3d.global.shared::cta.bulk_group [%0, {%2, %3, %4}], [%1];" ::"l"(tm), "r"(src), "r"(c0), "r"(c1), "r"(c2) : "memory");
}
__device__ __forceinline__ void pf2d(const CUtensorMap* tm, int c0, int c1) {
  asm volatile("cp.async.bulk.prefetch.tensor.2d.L2.global [%0, {%1, %2}];" ::"l"(tm), "r"(c0), "r"(c1) : "memory");
}
__device__ __forceinline__ void pf3d(const CUtensorMap* tm, int c0, int c1) {
  asm volatile("cp.async.bulk.prefetch.tensor.3d.L2.global [%0, {%1, %2, %3}];" ::"l"(tm), "r"(c0), "r"(c1), "r"(0) : "memory");
}
__device__ __forceinline__ void cp_async16(uint32_t dst, const void* src) { asm volatile("cp.async.cg.shared.global [%0], [%1], 16;" ::"r"(dst), "l"(src) : "memory"); }
__device__ __forceinline__ uint32_t ldg_nc(const void* p) { uint32_t v; asm volatile("ld.global.nc.u32 %0, [%1];" : "=r"(v) : "l"(p) : "memory"); return v; }
__device__ __forceinline__ void bulk_commit() { asm volatile("cp.async.bulk.commit_group;" ::: "memory"); }
__device__ __forceinline__ void bulk_wait_read() { asm volatile("cp.async.bulk.wait_group.read 0;" ::: "memory"); }
__device__ __forceinline__ void bulk_wait() { asm volatile("cp.async.bulk.wait_group 0;" ::: "memory"); }
__device__ __forceinline__ void prefetch_tm(const CUtensorMap* tm) { asm volatile("prefetch.tensormap [%0];" ::"l"(tm) : "memory"); }
__device__ __forceinline__ void prefetch_l2(const void* p, uint32_t bytes) { asm volatile("cp.async.bulk.prefetch.L2.global [%0], %1;" ::"l"(p), "r"(bytes) : "memory"); }
__device__ __forceinline__ unsigned ld_relaxed(const unsigned* p) { unsigned v; asm volatile("ld.relaxed.gpu.global.u32 %0, [%1];" : "=r"(v) : "l"(p) : "memory"); return v; }
__device__ __forceinline__ uint4 ld_relaxed4(const uint4* p) {
  uint4 v; asm volatile("ld.relaxed.gpu.global.v4.u32 {%0,%1,%2,%3}, [%4];" : "=r"(v.x), "=r"(v.y), "=r"(v.z), "=r"(v.w) : "l"(p) : "memory"); return v;
}
__device__ __forceinline__ void st_relaxed4(uint4* p, uint4 v) {
  asm volatile("st.relaxed.gpu.global.v4.u32 [%0], {%1,%2,%3,%4};" ::"l"(p), "r"(v.x), "r"(v.y), "r"(v.z), "r"(v.w) : "memory");
}
__device__ __forceinline__ void red_release(unsigned* p, unsigned v) { asm volatile("red.release.gpu.global.add.u32 [%0], %1;" ::"l"(p), "r"(v) : "memory"); }
__device__ __forceinline__ void wait_flag(const unsigned* p, unsigned target) {
  asm volatile(
      "{\n.reg .pred p;\n.reg .u32 c, v;\nmov.u32 c, 0;\n"
      "LAB_WAIT:\n"
      "ld.acquire.gpu.global.u32 v, [%0];\n"
      "sub.u32 v, v, %1;\n"
      "setp.ge.s32 p, v, 0;\n"
      "@p bra DONE;\n"
      "add.u32 c, c, 1;\n"
      "setp.lt.u32 p, c, 0x2000000;\n"
      "@p bra LAB_WAIT;\n"
      "trap;\n"
      "DONE:\n}" ::"l"(p), "r"(target) : "memory");
}
__device__ __forceinline__ bool elect_one() {
  uint32_t p;
  asm volatile("{\n.reg .pred P;\nelect.sync _|P, 0xffffffff;\nselp.u32 %0, 1, 0, P;\n}" : "=r"(p));
  return p != 0;
}
__device__ __forceinline__ int opaque(int x) { asm volatile("" : "+r"(x)); return x; }
__device__ __forceinline__ void bar_sync(int id, int n) { asm volatile("bar.sync %0, %1;" ::"r"(id), "r"(n) : "memory"); }
__device__ __forceinline__ void bar_arrive(int id, int n) { asm volatile("bar.arrive %0, %1;" ::"r"(id), "r"(n) : "memory"); }
__device__ __forceinline__ void fence_async() { asm volatile("fence.proxy.async.global;" ::: "memory"); }
__device__ __forceinline__ void fence_async_smem() { asm volatile("fence.proxy.async.shared::cta;" ::: "memory"); }
__device__ __forceinline__ void cluster_arrive() { asm volatile("barrier.cluster.arrive.relaxed.aligned;" ::: "memory"); }
__device__ __forceinline__ void cluster_wait() { asm volatile("barrier.cluster.wait.aligned;" ::: "memory"); }
__device__ __forceinline__ uint64_t mkdesc(uint32_t addr, uint32_t lbo, uint32_t sbo) {
  return (uint64_t)((addr & 0x3FFFF) >> 4) | ((uint64_t)(lbo >> 4) << 16) | ((uint64_t)(sbo >> 4) << 32) | (1ull << 62);
}
__device__ __forceinline__ uint32_t pack_bf16(float lo, float hi) { uint32_t r; asm("cvt.rn.bf16x2.f32 %0, %1, %2;" : "=r"(r) : "f"(hi), "f"(lo)); return r; }
__device__ __forceinline__ uint32_t mul_bf16x2(uint32_t a, uint32_t b) { uint32_t r; asm("mul.rn.bf16x2 %0, %1, %2;" : "=r"(r) : "r"(a), "r"(b)); return r; }
__device__ __forceinline__ uint32_t fma_relu_bf16x2(uint32_t a, uint32_t b, uint32_t c) {
  uint32_t r; asm("fma.rn.relu.bf16x2 %0, %1, %2, %3;" : "=r"(r) : "r"(a), "r"(b), "r"(c)); return r;
}
__device__ __forceinline__ float bf_lo(uint32_t v) { return __uint_as_float(v << 16); }
__device__ __forceinline__ float bf_hi(uint32_t v) { return __uint_as_float(v & 0xffff0000u); }
__device__ __forceinline__ void stsm_x4(uint32_t a, uint32_t r0, uint32_t r1, uint32_t r2, uint32_t r3) {
  asm volatile("stmatrix.sync.aligned.m8n8.x4.shared.b16 [%0], {%1, %2, %3, %4};" ::"r"(a), "r"(r0), "r"(r1), "r"(r2), "r"(r3) : "memory");
}
__device__ __forceinline__ void ldsm_x4(uint32_t a, uint32_t (&r)[4]) {
  asm volatile("ldmatrix.sync.aligned.m8n8.x4.shared.b16 {%0, %1, %2, %3}, [%4];" : "=r"(r[0]), "=r"(r[1]), "=r"(r[2]), "=r"(r[3]) : "r"(a) : "memory");
}
__device__ __forceinline__ void ldsm_x4_t(uint32_t a, uint32_t (&r)[4]) {
  asm volatile("ldmatrix.sync.aligned.m8n8.x4.trans.shared.b16 {%0, %1, %2, %3}, [%4];" : "=r"(r[0]), "=r"(r[1]), "=r"(r[2]), "=r"(r[3]) : "r"(a) : "memory");
}
__device__ __forceinline__ void mma16(float (&d)[4], uint32_t a0, uint32_t a1, uint32_t a2, uint32_t a3, uint32_t b0, uint32_t b1) {
  asm volatile("mma.sync.aligned.m16n8k16.row.col.f32.bf16.bf16.f32 {%0,%1,%2,%3}, {%4,%5,%6,%7}, {%8,%9}, {%0,%1,%2,%3};"
               : "+f"(d[0]), "+f"(d[1]), "+f"(d[2]), "+f"(d[3]) : "r"(a0), "r"(a1), "r"(a2), "r"(a3), "r"(b0), "r"(b1));
}
__device__ __forceinline__ void mma8(float (&d)[4], uint32_t a0, uint32_t a1, uint32_t b0) {
  asm volatile("mma.sync.aligned.m16n8k8.row.col.f32.bf16.bf16.f32 {%0,%1,%2,%3}, {%4,%5}, {%6}, {%0,%1,%2,%3};"
               : "+f"(d[0]), "+f"(d[1]), "+f"(d[2]), "+f"(d[3]) : "r"(a0), "r"(a1), "r"(b0));
}
__device__ __forceinline__ void sts128(uint32_t a, uint4 v) { asm volatile("st.shared.v4.u32 [%0], {%1,%2,%3,%4};" ::"r"(a), "r"(v.x), "r"(v.y), "r"(v.z), "r"(v.w) : "memory"); }
__device__ __forceinline__ uint4 lds128(uint32_t a) {
  uint4 v; asm volatile("ld.shared.v4.u32 {%0,%1,%2,%3}, [%4];" : "=r"(v.x), "=r"(v.y), "=r"(v.z), "=r"(v.w) : "r"(a) : "memory"); return v;
}
__device__ __forceinline__ void sts32(uint32_t a, uint32_t v) { asm volatile("st.shared.u32 [%0], %1;" ::"r"(a), "r"(v) : "memory"); }
__device__ __forceinline__ void sts32f(uint32_t a, float v) { asm volatile("st.shared.f32 [%0], %1;" ::"r"(a), "f"(v) : "memory"); }
__device__ __forceinline__ uint32_t lds32(uint32_t a) { uint32_t v; asm volatile("ld.shared.u32 %0, [%1];" : "=r"(v) : "r"(a) : "memory"); return v; }
__device__ __forceinline__ float lds32f(uint32_t a) { float v; asm volatile("ld.shared.f32 %0, [%1];" : "=f"(v) : "r"(a) : "memory"); return v; }
__device__ __forceinline__ float ex2(float x) { float r; asm("ex2.approx.ftz.f32 %0, %1;" : "=f"(r) : "f"(x)); return r; }
__device__ __forceinline__ float rcp(float x) { float r; asm("rcp.approx.ftz.f32 %0, %1;" : "=f"(r) : "f"(x)); return r; }

template <int M> __device__ __forceinline__ void wgmma_n160(float (&d)[M], uint64_t da, uint64_t db, int scale_d) {
  asm volatile("{\n.reg .pred p;\nsetp.ne.b32 p, %82, 0;\n"
    "wgmma.mma_async.sync.aligned.m64n160k16.f32.bf16.bf16 "
    "{%0, %1, %2, %3, %4, %5, %6, %7, %8, %9, %10, %11, %12, %13, %14, %15, "
    "%16, %17, %18, %19, %20, %21, %22, %23, %24, %25, %26, %27, %28, %29, %30, %31, "
    "%32, %33, %34, %35, %36, %37, %38, %39, %40, %41, %42, %43, %44, %45, %46, %47, "
    "%48, %49, %50, %51, %52, %53, %54, %55, %56, %57, %58, %59, %60, %61, %62, %63, "
    "%64, %65, %66, %67, %68, %69, %70, %71, %72, %73, %74, %75, %76, %77, %78, %79}, "
    "%80, %81, p, 1, 1, 0, 1;\n}\n"
    : "+f"(d[0]), "+f"(d[1]), "+f"(d[2]), "+f"(d[3]), "+f"(d[4]), "+f"(d[5]), "+f"(d[6]), "+f"(d[7]),
      "+f"(d[8]), "+f"(d[9]), "+f"(d[10]), "+f"(d[11]), "+f"(d[12]), "+f"(d[13]), "+f"(d[14]), "+f"(d[15]),
      "+f"(d[16]), "+f"(d[17]), "+f"(d[18]), "+f"(d[19]), "+f"(d[20]), "+f"(d[21]), "+f"(d[22]), "+f"(d[23]),
      "+f"(d[24]), "+f"(d[25]), "+f"(d[26]), "+f"(d[27]), "+f"(d[28]), "+f"(d[29]), "+f"(d[30]), "+f"(d[31]),
      "+f"(d[32]), "+f"(d[33]), "+f"(d[34]), "+f"(d[35]), "+f"(d[36]), "+f"(d[37]), "+f"(d[38]), "+f"(d[39]),
      "+f"(d[40]), "+f"(d[41]), "+f"(d[42]), "+f"(d[43]), "+f"(d[44]), "+f"(d[45]), "+f"(d[46]), "+f"(d[47]),
      "+f"(d[48]), "+f"(d[49]), "+f"(d[50]), "+f"(d[51]), "+f"(d[52]), "+f"(d[53]), "+f"(d[54]), "+f"(d[55]),
      "+f"(d[56]), "+f"(d[57]), "+f"(d[58]), "+f"(d[59]), "+f"(d[60]), "+f"(d[61]), "+f"(d[62]), "+f"(d[63]),
      "+f"(d[64]), "+f"(d[65]), "+f"(d[66]), "+f"(d[67]), "+f"(d[68]), "+f"(d[69]), "+f"(d[70]), "+f"(d[71]),
      "+f"(d[72]), "+f"(d[73]), "+f"(d[74]), "+f"(d[75]), "+f"(d[76]), "+f"(d[77]), "+f"(d[78]), "+f"(d[79])
    : "l"(da), "l"(db), "r"(scale_d));
}
template <int M> __device__ __forceinline__ void wgmma_n208(float (&d)[M], uint64_t da, uint64_t db, int scale_d) {
  asm volatile("{\n.reg .pred p;\nsetp.ne.b32 p, %106, 0;\n"
    "wgmma.mma_async.sync.aligned.m64n208k16.f32.bf16.bf16 "
    "{%0, %1, %2, %3, %4, %5, %6, %7, %8, %9, %10, %11, %12, %13, %14, %15, "
    "%16, %17, %18, %19, %20, %21, %22, %23, %24, %25, %26, %27, %28, %29, %30, %31, "
    "%32, %33, %34, %35, %36, %37, %38, %39, %40, %41, %42, %43, %44, %45, %46, %47, "
    "%48, %49, %50, %51, %52, %53, %54, %55, %56, %57, %58, %59, %60, %61, %62, %63, "
    "%64, %65, %66, %67, %68, %69, %70, %71, %72, %73, %74, %75, %76, %77, %78, %79, "
    "%80, %81, %82, %83, %84, %85, %86, %87, %88, %89, %90, %91, %92, %93, %94, %95, "
    "%96, %97, %98, %99, %100, %101, %102, %103}, "
    "%104, %105, p, 1, 1, 0, 1;\n}\n"
    : "+f"(d[0]), "+f"(d[1]), "+f"(d[2]), "+f"(d[3]), "+f"(d[4]), "+f"(d[5]), "+f"(d[6]), "+f"(d[7]),
      "+f"(d[8]), "+f"(d[9]), "+f"(d[10]), "+f"(d[11]), "+f"(d[12]), "+f"(d[13]), "+f"(d[14]), "+f"(d[15]),
      "+f"(d[16]), "+f"(d[17]), "+f"(d[18]), "+f"(d[19]), "+f"(d[20]), "+f"(d[21]), "+f"(d[22]), "+f"(d[23]),
      "+f"(d[24]), "+f"(d[25]), "+f"(d[26]), "+f"(d[27]), "+f"(d[28]), "+f"(d[29]), "+f"(d[30]), "+f"(d[31]),
      "+f"(d[32]), "+f"(d[33]), "+f"(d[34]), "+f"(d[35]), "+f"(d[36]), "+f"(d[37]), "+f"(d[38]), "+f"(d[39]),
      "+f"(d[40]), "+f"(d[41]), "+f"(d[42]), "+f"(d[43]), "+f"(d[44]), "+f"(d[45]), "+f"(d[46]), "+f"(d[47]),
      "+f"(d[48]), "+f"(d[49]), "+f"(d[50]), "+f"(d[51]), "+f"(d[52]), "+f"(d[53]), "+f"(d[54]), "+f"(d[55]),
      "+f"(d[56]), "+f"(d[57]), "+f"(d[58]), "+f"(d[59]), "+f"(d[60]), "+f"(d[61]), "+f"(d[62]), "+f"(d[63]),
      "+f"(d[64]), "+f"(d[65]), "+f"(d[66]), "+f"(d[67]), "+f"(d[68]), "+f"(d[69]), "+f"(d[70]), "+f"(d[71]),
      "+f"(d[72]), "+f"(d[73]), "+f"(d[74]), "+f"(d[75]), "+f"(d[76]), "+f"(d[77]), "+f"(d[78]), "+f"(d[79]),
      "+f"(d[80]), "+f"(d[81]), "+f"(d[82]), "+f"(d[83]), "+f"(d[84]), "+f"(d[85]), "+f"(d[86]), "+f"(d[87]),
      "+f"(d[88]), "+f"(d[89]), "+f"(d[90]), "+f"(d[91]), "+f"(d[92]), "+f"(d[93]), "+f"(d[94]), "+f"(d[95]),
      "+f"(d[96]), "+f"(d[97]), "+f"(d[98]), "+f"(d[99]), "+f"(d[100]), "+f"(d[101]), "+f"(d[102]), "+f"(d[103])
    : "l"(da), "l"(db), "r"(scale_d));
}
template <int M> __device__ __forceinline__ void wgmma_n224(float (&d)[M], uint64_t da, uint64_t db, int scale_d) {
  asm volatile("{\n.reg .pred p;\nsetp.ne.b32 p, %114, 0;\n"
    "wgmma.mma_async.sync.aligned.m64n224k16.f32.bf16.bf16 "
    "{%0, %1, %2, %3, %4, %5, %6, %7, %8, %9, %10, %11, %12, %13, %14, %15, "
    "%16, %17, %18, %19, %20, %21, %22, %23, %24, %25, %26, %27, %28, %29, %30, %31, "
    "%32, %33, %34, %35, %36, %37, %38, %39, %40, %41, %42, %43, %44, %45, %46, %47, "
    "%48, %49, %50, %51, %52, %53, %54, %55, %56, %57, %58, %59, %60, %61, %62, %63, "
    "%64, %65, %66, %67, %68, %69, %70, %71, %72, %73, %74, %75, %76, %77, %78, %79, "
    "%80, %81, %82, %83, %84, %85, %86, %87, %88, %89, %90, %91, %92, %93, %94, %95, "
    "%96, %97, %98, %99, %100, %101, %102, %103, %104, %105, %106, %107, %108, %109, %110, %111}, "
    "%112, %113, p, 1, 1, 0, 1;\n}\n"
    : "+f"(d[0]), "+f"(d[1]), "+f"(d[2]), "+f"(d[3]), "+f"(d[4]), "+f"(d[5]), "+f"(d[6]), "+f"(d[7]),
      "+f"(d[8]), "+f"(d[9]), "+f"(d[10]), "+f"(d[11]), "+f"(d[12]), "+f"(d[13]), "+f"(d[14]), "+f"(d[15]),
      "+f"(d[16]), "+f"(d[17]), "+f"(d[18]), "+f"(d[19]), "+f"(d[20]), "+f"(d[21]), "+f"(d[22]), "+f"(d[23]),
      "+f"(d[24]), "+f"(d[25]), "+f"(d[26]), "+f"(d[27]), "+f"(d[28]), "+f"(d[29]), "+f"(d[30]), "+f"(d[31]),
      "+f"(d[32]), "+f"(d[33]), "+f"(d[34]), "+f"(d[35]), "+f"(d[36]), "+f"(d[37]), "+f"(d[38]), "+f"(d[39]),
      "+f"(d[40]), "+f"(d[41]), "+f"(d[42]), "+f"(d[43]), "+f"(d[44]), "+f"(d[45]), "+f"(d[46]), "+f"(d[47]),
      "+f"(d[48]), "+f"(d[49]), "+f"(d[50]), "+f"(d[51]), "+f"(d[52]), "+f"(d[53]), "+f"(d[54]), "+f"(d[55]),
      "+f"(d[56]), "+f"(d[57]), "+f"(d[58]), "+f"(d[59]), "+f"(d[60]), "+f"(d[61]), "+f"(d[62]), "+f"(d[63]),
      "+f"(d[64]), "+f"(d[65]), "+f"(d[66]), "+f"(d[67]), "+f"(d[68]), "+f"(d[69]), "+f"(d[70]), "+f"(d[71]),
      "+f"(d[72]), "+f"(d[73]), "+f"(d[74]), "+f"(d[75]), "+f"(d[76]), "+f"(d[77]), "+f"(d[78]), "+f"(d[79]),
      "+f"(d[80]), "+f"(d[81]), "+f"(d[82]), "+f"(d[83]), "+f"(d[84]), "+f"(d[85]), "+f"(d[86]), "+f"(d[87]),
      "+f"(d[88]), "+f"(d[89]), "+f"(d[90]), "+f"(d[91]), "+f"(d[92]), "+f"(d[93]), "+f"(d[94]), "+f"(d[95]),
      "+f"(d[96]), "+f"(d[97]), "+f"(d[98]), "+f"(d[99]), "+f"(d[100]), "+f"(d[101]), "+f"(d[102]), "+f"(d[103]),
      "+f"(d[104]), "+f"(d[105]), "+f"(d[106]), "+f"(d[107]), "+f"(d[108]), "+f"(d[109]), "+f"(d[110]), "+f"(d[111])
    : "l"(da), "l"(db), "r"(scale_d));
}
template <int M> __device__ __forceinline__ void wgmma_n248(float (&d)[M], uint64_t da, uint64_t db, int scale_d) {
  asm volatile("{\n.reg .pred p;\nsetp.ne.b32 p, %126, 0;\n"
    "wgmma.mma_async.sync.aligned.m64n248k16.f32.bf16.bf16 "
    "{%0, %1, %2, %3, %4, %5, %6, %7, %8, %9, %10, %11, %12, %13, %14, %15, "
    "%16, %17, %18, %19, %20, %21, %22, %23, %24, %25, %26, %27, %28, %29, %30, %31, "
    "%32, %33, %34, %35, %36, %37, %38, %39, %40, %41, %42, %43, %44, %45, %46, %47, "
    "%48, %49, %50, %51, %52, %53, %54, %55, %56, %57, %58, %59, %60, %61, %62, %63, "
    "%64, %65, %66, %67, %68, %69, %70, %71, %72, %73, %74, %75, %76, %77, %78, %79, "
    "%80, %81, %82, %83, %84, %85, %86, %87, %88, %89, %90, %91, %92, %93, %94, %95, "
    "%96, %97, %98, %99, %100, %101, %102, %103, %104, %105, %106, %107, %108, %109, %110, %111, "
    "%112, %113, %114, %115, %116, %117, %118, %119, %120, %121, %122, %123}, "
    "%124, %125, p, 1, 1, 0, 1;\n}\n"
    : "+f"(d[0]), "+f"(d[1]), "+f"(d[2]), "+f"(d[3]), "+f"(d[4]), "+f"(d[5]), "+f"(d[6]), "+f"(d[7]),
      "+f"(d[8]), "+f"(d[9]), "+f"(d[10]), "+f"(d[11]), "+f"(d[12]), "+f"(d[13]), "+f"(d[14]), "+f"(d[15]),
      "+f"(d[16]), "+f"(d[17]), "+f"(d[18]), "+f"(d[19]), "+f"(d[20]), "+f"(d[21]), "+f"(d[22]), "+f"(d[23]),
      "+f"(d[24]), "+f"(d[25]), "+f"(d[26]), "+f"(d[27]), "+f"(d[28]), "+f"(d[29]), "+f"(d[30]), "+f"(d[31]),
      "+f"(d[32]), "+f"(d[33]), "+f"(d[34]), "+f"(d[35]), "+f"(d[36]), "+f"(d[37]), "+f"(d[38]), "+f"(d[39]),
      "+f"(d[40]), "+f"(d[41]), "+f"(d[42]), "+f"(d[43]), "+f"(d[44]), "+f"(d[45]), "+f"(d[46]), "+f"(d[47]),
      "+f"(d[48]), "+f"(d[49]), "+f"(d[50]), "+f"(d[51]), "+f"(d[52]), "+f"(d[53]), "+f"(d[54]), "+f"(d[55]),
      "+f"(d[56]), "+f"(d[57]), "+f"(d[58]), "+f"(d[59]), "+f"(d[60]), "+f"(d[61]), "+f"(d[62]), "+f"(d[63]),
      "+f"(d[64]), "+f"(d[65]), "+f"(d[66]), "+f"(d[67]), "+f"(d[68]), "+f"(d[69]), "+f"(d[70]), "+f"(d[71]),
      "+f"(d[72]), "+f"(d[73]), "+f"(d[74]), "+f"(d[75]), "+f"(d[76]), "+f"(d[77]), "+f"(d[78]), "+f"(d[79]),
      "+f"(d[80]), "+f"(d[81]), "+f"(d[82]), "+f"(d[83]), "+f"(d[84]), "+f"(d[85]), "+f"(d[86]), "+f"(d[87]),
      "+f"(d[88]), "+f"(d[89]), "+f"(d[90]), "+f"(d[91]), "+f"(d[92]), "+f"(d[93]), "+f"(d[94]), "+f"(d[95]),
      "+f"(d[96]), "+f"(d[97]), "+f"(d[98]), "+f"(d[99]), "+f"(d[100]), "+f"(d[101]), "+f"(d[102]), "+f"(d[103]),
      "+f"(d[104]), "+f"(d[105]), "+f"(d[106]), "+f"(d[107]), "+f"(d[108]), "+f"(d[109]), "+f"(d[110]), "+f"(d[111]),
      "+f"(d[112]), "+f"(d[113]), "+f"(d[114]), "+f"(d[115]), "+f"(d[116]), "+f"(d[117]), "+f"(d[118]), "+f"(d[119]),
      "+f"(d[120]), "+f"(d[121]), "+f"(d[122]), "+f"(d[123])
    : "l"(da), "l"(db), "r"(scale_d));
}


template <int N> __device__ __forceinline__ void reg_fence(float (&d)[N]) {
#pragma unroll
  for (int x = 0; x < N; x++) asm volatile("" : "+f"(d[x])::"memory");
}
template <int N, int M> __device__ __forceinline__ void wg_mma(float (&d)[M], uint64_t da, uint64_t db, int sc) {
  if constexpr (N == 160) wgmma_n160(d, da, db, sc);
  else if constexpr (N == 208) wgmma_n208(d, da, db, sc);
  else if constexpr (N == 224) wgmma_n224(d, da, db, sc);
  else wgmma_n248(d, da, db, sc);
}

struct Pipe { uint32_t na, sb, pb; };

template <int N, int M, int RING, bool TRAIL, class F>
__device__ __forceinline__ void mainloop(float (&acc)[M], int nblk, Pipe& p, uint32_t sbase, int wg, bool elect, bool zero, int norel, int hold, F&& tail) {
  const uint32_t bars = sbase + OFF_BAR;
  constexpr bool OUTP = RING == 2;
  const uint64_t dA0 = mkdesc(sbase + OFF_A + wg * 8192, 16, 1024);
  const uint64_t dB0 = mkdesc(sbase + OFF_B, 8192, 1024);
  uint32_t prevA = 0, prevB = 0;
  reg_fence(acc);
#pragma unroll 1
  for (int kb = 0; kb < nblk; ++kb) {
    if (TRAIL && kb == hold) {
      asm volatile("wgmma.wait_group.sync.aligned 0;" ::: "memory");
      if (elect && prevA) { mbar_arrive(prevA); mbar_arrive_cluster(prevB, 0); mbar_arrive_cluster(prevB, 1); }
      prevA = 0;
      bar_sync(3, 256);
    }
    if (RING == 0) {
      asm volatile("{\n.reg .pred p;\nsetp.ne.s32 p, %0, 0;\n@p bra SKIP;\ncp.async.wait_all;\nfence.proxy.async.shared::cta;\nbar.sync 4, 256;\nSKIP:\n}"
                   ::"r"(kb) : "memory");
    }
    const uint32_t sa = p.na & 3;
    mbar_wait(bars + (BAR_AF + sa) * 8, (p.na >> 2) & 1);
    const uint32_t sb = RING == 0 ? sa : p.sb;
    mbar_wait(bars + (BAR_BF + sb) * 8, RING == 0 ? (p.na >> 2) & 1 : p.pb);
    const uint64_t da = dA0 + (uint64_t)(sa * 1024);
    const uint64_t db = dB0 + (uint64_t)(RING == 0 ? (sb == 3 ? B3_OFF >> 4 : sb * 2048) : sb * (OUTP ? 1536 : 2048));
    reg_fence(acc);
    asm volatile("wgmma.fence.sync.aligned;" ::: "memory");
    wg_mma<N>(acc, da, db, (kb > 0 || !zero) ? 1 : 0);
    asm volatile("wgmma.commit_group.sync.aligned;" ::: "memory");
    if (!TRAIL || prevA) {
      asm volatile("wgmma.wait_group.sync.aligned 1;" ::: "memory");
      if (elect && prevA) { mbar_arrive(prevA); mbar_arrive_cluster(prevB, 0); mbar_arrive_cluster(prevB, 1); }
    }
    wg_mma<N>(acc, da + 2, db + 128, 1);
    wg_mma<N>(acc, da + 4, db + 256, 1);
    wg_mma<N>(acc, da + 6, db + 384, 1);
    asm volatile("wgmma.commit_group.sync.aligned;" ::: "memory");
    prevA = (!TRAIL || kb < nblk - norel) ? bars + (BAR_AE + sa) * 8 : 0;
    prevB = bars + (BAR_BE + sb) * 8;
    ++p.na;
    if (RING == 2) {
      p.sb = (p.sb + 1) & 3;
      if (p.sb == 0) p.pb ^= 1;
    } else if (RING == 1) {
      if (++p.sb == 3) { p.sb = 0; p.pb ^= 1; }
    }
  }
  tail();
  asm volatile("wgmma.wait_group.sync.aligned 0;" ::: "memory");
  reg_fence(acc);
  if (elect && prevA) { mbar_arrive(prevA); mbar_arrive_cluster(prevB, 0); mbar_arrive_cluster(prevB, 1); }
}

struct Role {
  int i, c, s, rank;
  int full0, part0;
};

__device__ __forceinline__ void softmax4(const float (&s0)[4], const float (&s1)[4], const float (&s2)[4], bool p0, bool p1, uint32_t msk,
                                         uint32_t& pa0, uint32_t& pa2, uint32_t& pa3, uint32_t& pb1) {
  constexpr float SC = 0.22360679774997896f * 1.4426950408889634f;
  const float l0 = p0 ? s1[0] : s0[0], l1 = p1 ? s1[1] : s0[1], h0 = p0 ? s2[2] : s1[2], h1 = p1 ? s2[3] : s1[3];
  float ml = fmaxf(l0, l1), mh = fmaxf(h0, h1);
  ml = fmaxf(ml, __shfl_xor_sync(0xffffffffu, ml, 1)); mh = fmaxf(mh, __shfl_xor_sync(0xffffffffu, mh, 1));
  ml = fmaxf(ml, __shfl_xor_sync(0xffffffffu, ml, 2)); mh = fmaxf(mh, __shfl_xor_sync(0xffffffffu, mh, 2));
  ml *= SC; mh *= SC;
  const uint32_t pl = pack_bf16(ex2(fmaf(l0, SC, -ml)), ex2(fmaf(l1, SC, -ml)));
  const uint32_t ph = pack_bf16(ex2(fmaf(h0, SC, -mh)), ex2(fmaf(h1, SC, -mh)));
  pa0 = pl & ~msk; pa2 = pl & msk; pa3 = ph & ~msk; pb1 = ph & msk;
}

__device__ __forceinline__ void attention(const uint32_t (&q)[5][4], uint32_t stg, uint32_t gsm, int wg, int warp, int lane, bool first) {
  const int t = lane & 3, g = lane >> 2, lg = lane >> 3;
  const uint32_t kb = stg + STG_KV + wg * KPAR + warp * 256 + (lane & 7) * 16;
  const uint32_t p1 = kb + (lg + (lg >> 1)) * KC, p2 = kb + min(lg, 2) * 128, p3 = kb + (lg >> 1) * KC + (lg & 1) * 128;
  const bool p0 = 2 * t <= g, p1_ = 2 * t + 1 <= g;
  const uint32_t msk = (p0 ? 0xffffu : 0u) | (p1_ ? 0xffff0000u : 0u);
  const uint32_t mA = t < 2 ? 0xffffffffu : 0u;
  const float ninf = first ? -INFINITY : 0.f;
  const float ezl = lds32f(gsm + (2 * (warp * 16 + g) + wg) * 4), ezh = lds32f(gsm + (2 * (warp * 16 + g + 8) + wg) * 4);
  const uint32_t ob = stg + (wg * 4 + warp) * 2560 + (lane & 15) * 160 + (lane >> 4) * 16;
  uint32_t ores[2][10];
#pragma unroll
  for (int hp = 0; hp < 2; hp++) {
#define QF(x, half) q[(5 * hp + (x)) >> 1][(((5 * hp + (x)) & 1) << 1) + (half)]
    uint32_t ka[3][4], k2[4];
#pragma unroll
    for (int j = 0; j < 3; j++) ldsm_x4(p1 + 5 * hp * KC + j * 128, ka[j]);
    ldsm_x4(p2 + (5 * hp + 2) * KC, k2);
    float sa[3][4], sb[3][4];
#pragma unroll
    for (int j = 0; j < 3; j++) {
      sa[j][0] = sa[j][1] = sb[j][0] = sb[j][1] = (j == 0) ? ninf : 0.f;
      sa[j][2] = sa[j][3] = sb[j][2] = sb[j][3] = 0.f;
      mma16(sa[j], QF(0, 0), QF(0, 1), QF(1, 0), QF(1, 1), ka[j][0], ka[j][1]);
      mma16(sb[j], QF(3, 0), QF(3, 1), QF(4, 0), QF(4, 1), ka[j][2], ka[j][3]);
      mma8(sa[j], QF(2, 0) & mA, QF(2, 1) & mA, k2[j]);
      mma8(sb[j], QF(2, 0) & ~mA, QF(2, 1) & ~mA, k2[j]);
    }
    uint32_t va[4], vb[4], v2[4], vc[4];
    ldsm_x4_t(p3 + (10 + 5 * hp) * KC, va);
    ldsm_x4_t(p3 + (13 + 5 * hp) * KC, vb);
    ldsm_x4_t(p2 + (12 + 5 * hp) * KC, v2);
    ldsm_x4_t(p1 + (10 + 5 * hp) * KC + 256, vc);
    uint32_t a0, a2, a3, a1, b0, b2, b3, b1;
    softmax4(sa[0], sa[1], sa[2], p0, p1_, msk, a0, a2, a3, a1);
    softmax4(sb[0], sb[1], sb[2], p0, p1_, msk, b0, b2, b3, b1);
    constexpr uint32_t ONE = 0x3f803f80u;
    float o[6][4], su[2][4];
#pragma unroll
    for (int c = 0; c < 6; c++) o[c][0] = o[c][1] = o[c][2] = o[c][3] = 0.f;
#pragma unroll
    for (int c = 0; c < 2; c++) su[c][0] = su[c][1] = su[c][2] = su[c][3] = 0.f;
    mma16(su[0], a0, 0, a2, a3, ONE, ONE); mma16(su[1], b0, 0, b2, b3, ONE, ONE);
    mma8(su[0], 0, a1, ONE); mma8(su[1], 0, b1, ONE);
    mma16(o[0], a0, 0, a2, a3, va[0], va[1]); mma16(o[1], a0, 0, a2, a3, va[2], va[3]); mma16(o[2], a0, 0, a2, a3, v2[0], v2[1]);
    mma16(o[3], b0, 0, b2, b3, v2[0], v2[1]); mma16(o[4], b0, 0, b2, b3, vb[0], vb[1]); mma16(o[5], b0, 0, b2, b3, vb[2], vb[3]);
    mma8(o[0], 0, a1, vc[0]); mma8(o[1], 0, a1, vc[1]); mma8(o[2], 0, a1, v2[2]);
    mma8(o[3], 0, b1, v2[2]); mma8(o[4], 0, b1, vc[2]); mma8(o[5], 0, b1, vc[3]);
    const float ral = ezl * rcp(su[0][0]), rah = ezh * rcp(su[0][2]), rbl = ezl * rcp(su[1][0]), rbh = ezh * rcp(su[1][2]);
    const float rml = t < 2 ? ral : rbl, rmh = t < 2 ? rah : rbh;
    ores[hp][0] = pack_bf16(o[0][0] * ral, o[0][1] * ral); ores[hp][1] = pack_bf16(o[0][2] * rah, o[0][3] * rah);
    ores[hp][2] = pack_bf16(o[1][0] * ral, o[1][1] * ral); ores[hp][3] = pack_bf16(o[1][2] * rah, o[1][3] * rah);
    ores[hp][4] = pack_bf16((t < 2 ? o[2][0] : o[3][0]) * rml, (t < 2 ? o[2][1] : o[3][1]) * rml);
    ores[hp][5] = pack_bf16((t < 2 ? o[2][2] : o[3][2]) * rmh, (t < 2 ? o[2][3] : o[3][3]) * rmh);
    ores[hp][6] = pack_bf16(o[4][0] * rbl, o[4][1] * rbl); ores[hp][7] = pack_bf16(o[4][2] * rbh, o[4][3] * rbh);
    ores[hp][8] = pack_bf16(o[5][0] * rbl, o[5][1] * rbl); ores[hp][9] = pack_bf16(o[5][2] * rbh, o[5][3] * rbh);
#undef QF
  }
  stsm_x4(ob, ores[0][0], ores[0][1], ores[0][2], ores[0][3]);
  stsm_x4(ob + 32, ores[0][4], ores[0][5], ores[0][6], ores[0][7]);
  stsm_x4(ob + 64, ores[0][8], ores[0][9], ores[1][0], ores[1][1]);
  stsm_x4(ob + 96, ores[1][2], ores[1][3], ores[1][4], ores[1][5]);
  stsm_x4(ob + 128, ores[1][6], ores[1][7], ores[1][8], ores[1][9]);
}

__device__ __forceinline__ void consumer(uint32_t sbase, int wg, const Role& R, const Maps& maps, const uint32_t (&bv)[28]) {
  int tid = threadIdx.x & 127;
  const bool elect = (tid == 0);
  const uint32_t bars = sbase + OFF_BAR;
  Pipe p{0, 2, 0};
#define LANE_VARS                                                                                     \
  tid = opaque(tid);                                                                                  \
  const int warp = tid >> 5, lane = tid & 31, t = lane & 3, g = lane >> 2;                            \
  const int r16 = ((lane >> 3) & 1) * 8 + (lane & 7);                                                 \
  const int srow = wg * 64 + warp * 16 + r16;                                                         \
  const int hi = lane >> 4;                                                                           \
  (void)t; (void)g; (void)srow; (void)hi;
  {
    float acc[112];
    const int nch = R.s ? 26 : 28;
    cluster_wait();
    uint32_t sa;
    auto tail1 = [&]() {
      tid = opaque(tid);
      const int lane = tid & 31, srow = wg * 64 + (tid >> 5) * 16 + ((lane >> 3) & 1) * 8 + (lane & 7);
      sa = sbase + OFF_STG + srow * 128 + (((lane >> 4) ^ (srow & 7)) << 4);
      mbar_wait(bars + BAR_RQ * 8, 0);
      mbar_wait(bars + (BAR_BE + 3) * 8, 1);
    };
    if (R.s == 0) mainloop<224, 112, 0, false>(acc, 10, p, sbase, wg, elect, true, 0, -1, tail1);
    else mainloop<208, 112, 0, false>(acc, 10, p, sbase, wg, elect, true, 0, -1, tail1);
    auto act2 = [&](float a, float b, uint32_t bias) {
      uint32_t r = fma_relu_bf16x2(pack_bf16(a, b), 0x3f803f80u, bias);
      return mul_bf16x2(r, r);
    };
#pragma unroll
    for (int c = 0; c < 28; c += 2) {
      if (c < 26 || c < nch)
        stsm_x4((sa ^ ((c & 7) << 4)) + (c >> 3) * 16384, act2(acc[4 * c], acc[4 * c + 1], bv[c]), act2(acc[4 * c + 2], acc[4 * c + 3], bv[c]),
                act2(acc[4 * c + 4], acc[4 * c + 5], bv[c + 1]), act2(acc[4 * c + 6], acc[4 * c + 7], bv[c + 1]));
    }
    __syncwarp();
    if ((tid & 31) == 0) mbar_arrive(bars + BAR_S1F * 8);
  }
  uint32_t qf[5][4];
  {
    float acc[124];
    uint32_t sk;
    mainloop<248, 124, 1, false>(acc, 10, p, sbase, wg, elect, true, 0, -1, [&]() {
      tid = opaque(tid);
      const int lane = tid & 31;
      sk = sbase + OFF_STG + STG_KV + wg * KPAR + ((tid >> 5) * 16 + 8 + ((lane >> 3) & 1) * 8 + (lane & 7)) * 16 + (lane >> 4) * KC;
      mbar_wait(bars + BAR_S1E * 8, 0);
    });
    const int warp = tid >> 5, lane = tid & 31, t = lane & 3, g = lane >> 2;
    if (t == 0) {
      const uint32_t ga = sbase + OFF_G + (2 * (warp * 16 + g) + wg) * 4;
      sts32f(ga, __expf(fminf(fmaxf(acc[120], -60.f), 60.f)));
      sts32f(ga + 64, __expf(fminf(fmaxf(acc[122], -60.f), 60.f)));
    }
#pragma unroll
    for (int c = 10; c < 30; c += 2)
      stsm_x4(sk + (c - 10) * KC, pack_bf16(acc[4 * c], acc[4 * c + 1]), pack_bf16(acc[4 * c + 2], acc[4 * c + 3]),
              pack_bf16(acc[4 * c + 4], acc[4 * c + 5]), pack_bf16(acc[4 * c + 6], acc[4 * c + 7]));
    __syncwarp();
    if (lane == 0) mbar_arrive(bars + BAR_S2F * 8);
#pragma unroll
    for (int c = 0; c < 5; c++)
#pragma unroll
      for (int x = 0; x < 4; x++) qf[c][x] = pack_bf16(acc[8 * c + 2 * x], acc[8 * c + 2 * x + 1]);
  }
  {
    float acc[80];
    const bool home = (wg == R.s);
    const int nblk = (R.s ? 19 : 18) - NPRE;
    p.sb = 0; p.pb = 0;
    if (!home) {
      const uint32_t b2a = sbase + OFF_B2 + (opaque(tid) & 3) * 4;
#pragma unroll
      for (int c = 0; c < 20; c++) {
        const uint32_t v = lds32(b2a + c * 16);
        acc[4 * c] = bf_lo(v); acc[4 * c + 1] = bf_hi(v); acc[4 * c + 2] = bf_lo(v); acc[4 * c + 3] = bf_hi(v);
      }
    }
    mainloop<160, 80, 2, false>(acc, NPRE, p, sbase, wg, elect, home, 0, -1, []() {});
    {
      LANE_VARS
      mbar_wait(bars + BAR_HALO * 8, 0);
      attention(qf, sbase + OFF_STG, sbase + OFF_G, wg, warp, lane, R.i == 0 && warp == 0);
      __syncwarp();
      if (lane == 0) mbar_arrive(bars + BAR_OF * 8);
    }
    LANE_VARS
    const int row_lo = wg * 64 + warp * 16 + g;
    const float glo = rcp(1.f + lds32f(sbase + OFF_G + row_lo * 4)), ghi = rcp(1.f + lds32f(sbase + OFF_G + (row_lo + 8) * 4));
    const int lrow = warp * 16 + r16;
    const uint32_t so = sbase + OFF_STG + wg * 24576 + lrow * 128 + ((hi ^ (lrow & 7)) << 4);
    mainloop<160, 80, 2, true>(acc, nblk, p, sbase, wg, elect, false, 4, home ? nblk - 4 : -1, [&]() {
      mbar_wait(bars + BAR_S2E * 8, 0);
    });
    if (!home) bar_arrive(3, 256);
    const bool odd = R.c & 1;
    const int x0 = R.c * 160 + (odd ? 32 : 0), x2 = R.c * 160 + (odd ? 0 : 128), y = R.i * 128 + wg * 64 + warp * 16;
    const uint32_t src = sbase + OFF_STG + wg * 24576 + warp * 2048;
    const bool lead = elect_one();
#pragma unroll
    for (int q = 0; q < 10; q++) {
      stsm_x4((so ^ (((2 * q) & 7) << 4)) + (q >> 2) * 8192,
              pack_bf16(acc[8 * q] * glo, acc[8 * q + 1] * glo), pack_bf16(acc[8 * q + 2] * ghi, acc[8 * q + 3] * ghi),
              pack_bf16(acc[8 * q + 4] * glo, acc[8 * q + 5] * glo), pack_bf16(acc[8 * q + 6] * ghi, acc[8 * q + 7] * ghi));
      if (q == 3 || q == 9) {
        fence_async_smem();
        __syncwarp();
        if (lead) {
          if (q == 3) {
            tma2d_reduce(&maps.of, src, x0, y);
          } else {
            tma2d_reduce(&maps.of, src + 8192, x0 + 64, y);
            tma2d_reduce(&maps.on, src + 16384, x2, y);
            bulk_commit();
            bulk_wait_read();
          }
        }
      }
    }
    __syncwarp();
  }
}

__device__ __forceinline__ void producer(uint32_t sbase, const Maps& maps, const Role& R,
                                         const __nv_bfloat16* w2, const __nv_bfloat16* wo) {
  const uint32_t bars = sbase + OFF_BAR;
  uint32_t na = 4, s = 0, ph = 0, lim = 4;
  const int jq = R.c * 2 + R.s, y0 = R.i * 128;
  {
    const CUtensorMap* ta = &maps.ax;
    const CUtensorMap* t0 = &maps.w1f;
    const CUtensorMap* t1 = R.rank ? &maps.w1n[R.s] : &maps.w1f;
    int x0 = R.full0 + R.rank * 64, x1 = R.rank ? R.part0 : R.full0 + 128, y = 256, xa = 256;
    const int ya = R.i * 64;
    uint32_t bytes = R.s ? 26624 : 28672;
    const uint32_t db = sbase + OFF_B + R.rank * 8192;
#pragma unroll 1
    for (int m = 4; m < 4 + PFI; m++) {
      if (m == jq) pf3d(ta, m * 64, ya);
      if (m == (R.i >> 1)) { pf2d(t0, x0, m * 64); pf2d(t1, x1, m * 64); }
    }
#pragma unroll 1
    for (int n = 4; n < 20; ++n) {
      if (n == 10) {
        mbar_wait(bars + BAR_RQ * 8, 0);
        t0 = t1 = &maps.wq;
        x0 = R.rank * 64; x1 = x0 + 128; y = jq * DM + 384; bytes = 32768;
        s = 2; ph = 1; lim = 3;
      }
      if (n == 14) { y = jq * DM; xa = 0; }
      const uint32_t sa = na & 3;
      mbar_wait(bars + (BAR_AE + sa) * 8, ((na >> 2) & 1) ^ 1);
      if (n >= 10 && n < 14) {
        mbar_arrive(bars + (BAR_AF + sa) * 8);
      } else {
        mbar_expect_tx(bars + (BAR_AF + sa) * 8, 16384);
        tma3d(sbase + OFF_A + sa * 16384, ta, bars + (BAR_AF + sa) * 8, xa, ya);
      }
      ++na;
      mbar_wait(bars + (BAR_BE + s) * 8, ph);
      const uint32_t fb = bars + (BAR_BF + s) * 8;
      mbar_expect_tx(fb, bytes);
      const uint32_t d = db + (s == 3 ? B3_OFF : s * 32768);
      tma2d_mc(d, t0, fb, x0, y);
      tma2d_mc(d + 16384, t1, fb, x1, y);
      if (n + PFD < 10 && n + PFD >= 4 + PFI) {
        if (((n + PFD) & 7) == jq) pf3d(ta, xa + PFD * 64, ya);
        if (((n + PFD) & 7) == (R.i >> 1)) { pf2d(t0, x0, y + PFD * 64); pf2d(t1, x1, y + PFD * 64); }
      }
      if (n == PFW) {
        prefetch_l2(reinterpret_cast<const uint8_t*>(w2) + blockIdx.x * 17280, 17280);
        prefetch_l2(reinterpret_cast<const uint8_t*>(wo) + blockIdx.x * 6400, 6400);
      }
      if (++s == lim) { s = 0; ph ^= 1; }
      xa += 64; y += 64;
    }
  }
  {
    const bool odd = R.c & 1;
    const int x0 = R.c * 160 + (odd ? 32 : 0), x2 = R.c * 160 + (odd ? 0 : 128);
    const CUtensorMap* tf = &maps.w2f;
    const CUtensorMap* tp = &maps.w2n;
    const int nh = R.s ? 14 : 13;
    int y = R.s ? 13 * 64 : 0, xa = DM + y;
    const uint32_t db = sbase + OFF_B + R.rank * 4096;
#pragma unroll 1
    for (int n = 0; n < nh + 5; ++n) {
      if (n == 0) mbar_wait(bars + BAR_RH * 8, 0);
      if (n == nh) {
        mbar_wait(bars + BAR_RO * 8, 0);
        tf = &maps.wof; tp = &maps.won;
        y = R.s * 320; xa = y;
      }
      const uint32_t sa = na & 3;
      mbar_wait(bars + (BAR_AE + sa) * 8, ((na >> 2) & 1) ^ 1);
      mbar_expect_tx(bars + (BAR_AF + sa) * 8, 16384);
      tma2d(sbase + OFF_A + sa * 16384, &maps.hf, bars + (BAR_AF + sa) * 8, xa, y0);
      ++na;
      const uint32_t sl = n & 3;
      mbar_wait(bars + (BAR_BE + sl) * 8, ((n >> 2) & 1) ^ 1);
      const uint32_t fb = bars + (BAR_BF + sl) * 8;
      mbar_expect_tx(fb, 20480);
      const uint32_t d = db + sl * 24576;
      const int yy = y + R.rank * 32;
      tma2d_mc(d, tf, fb, x0, yy);
      tma2d_mc(d + 8192, tf, fb, x0 + 64, yy);
      tma2d_mc(d + 16384, tp, fb, x2, yy);
      xa += 64; y += 64;
    }
  }
}

__device__ __forceinline__ void repack(uint32_t sbase, const Role& R, int half, const __nv_bfloat16* __restrict__ wqkv, const __nv_bfloat16* __restrict__ gate_w) {
  const int lane = threadIdx.x & 31;
  const int jq = R.c * 2 + R.s, r0 = R.i * 40 + half * 20;
  const int part = lane / 10;
  const uint8_t* src = reinterpret_cast<const uint8_t*>(wqkv + (size_t)r0 * (3 * DM) + part * DM + jq * 80 + (lane - part * 10) * 8);
  const uint32_t stg = sbase + OFF_STG + half * 10240;
  if (half == 0 && R.i < 15) {
    uint4* d = &g_halo[(R.i * 8 + jq) * 320 + lane];
#pragma unroll
    for (int k = 0; k < 10; k++) st_relaxed4(d + k * 32, make_uint4(0, 0, 0, 0));
  }
  uint32_t gv = 0;
  if (lane < 20) gv = __ldg(reinterpret_cast<const unsigned short*>(gate_w + r0) + lane);
  cluster_wait();
  if (lane < 30) {
#pragma unroll
    for (int k = 0; k < 20; k++)
      asm volatile("cp.async.cg.shared.global [%0], [%1], 16;" ::"r"(stg + k * 512 + lane * 16), "l"(src + k * (3 * DM * 2)) : "memory");
  }
  if (lane < 20) { sts128(stg + lane * 512 + 480, make_uint4(gv, 0, 0, 0)); sts128(stg + lane * 512 + 496, make_uint4(0, 0, 0, 0)); }
  asm volatile("cp.async.wait_all;" ::: "memory");
  fence_async_smem();
  __syncwarp();
  if (elect_one()) {
    asm volatile("cp.async.bulk.global.shared::cta.bulk_group [%0], [%1], %2;" ::"l"(g_wqkv + (size_t)(jq * DM + r0) * 256), "r"(stg), "r"(10240) : "memory");
    bulk_commit();
    bulk_wait();
    fence_async();
    red_release(g_rep + jq * 32, 1);
  }
  __syncwarp();
}

__device__ __forceinline__ void aux(uint32_t sbase, const Maps& maps, const Role& R, const __nv_bfloat16* __restrict__ b2, __nv_bfloat16* __restrict__ out) {
  const int lane = threadIdx.x & 31;
  const uint32_t bars = sbase + OFF_BAR;
  const uint32_t stg = sbase + OFF_STG;
  const int i = R.i, jq = R.c * 2 + R.s;
  unsigned* fl = g_flags + i * 32;
  const unsigned epoch = ld_relaxed(fl + FL_O) >> 3;
#pragma unroll
  for (int k = 0; k < 3; k++) {
    const int n = (k * 32 + lane) * 2;
    if (n < 160) {
      const int col = R.c * 160 + ((R.c & 1) ? (n < 128 ? n + 32 : n - 128) : n);
      sts32(sbase + OFF_B2 + n * 2, __ldg(reinterpret_cast<const uint32_t*>(b2 + col)));
    }
  }
  cluster_wait();
  __syncwarp();
  if (elect_one()) {
    wait_flag(g_rep + jq * 32, (epoch + 1) * 32);
    fence_async();
    mbar_arrive(bars + BAR_RQ * 8);
  }
  __syncwarp();
  if (lane < 20) {
    uint4* d = reinterpret_cast<uint4*>(out + (size_t)(i * 128 + R.s * 64) * DM + R.c * 160) + lane;
#pragma unroll 8
    for (int r = 0; r < 64; r++) d[r * (DM / 8)] = make_uint4(0, 0, 0, 0);
  }
  __syncwarp();
  if (elect_one()) {
    mbar_wait(bars + BAR_S1F * 8, 0);
    fence_async_smem();
#pragma unroll 1
    for (int k = 0; k < 7; k++) {
      if (k < 6) tma3d_store(&maps.hs, stg + k * 8192, DM + R.full0 + (k >> 1) * 64, i * 64, k & 1);
      else tma3d_store(&maps.hn[R.s], stg + 49152, DM + R.part0, i * 64);
      bulk_commit();
      if (k < 6) __nanosleep(HPACE);
    }
    bulk_wait_read();
    mbar_arrive(bars + BAR_S1E * 8);
    bulk_wait();
    fence_async();
    red_release(fl + FL_H, 1);
    wait_flag(fl + FL_H, (epoch + 1) * 8);
    fence_async();
    mbar_arrive(bars + BAR_RH * 8);
  }
  __syncwarp();
  mbar_wait(bars + BAR_S2F * 8, 0);
  {
    const uint32_t hs = stg + STG_KV + (lane >> 3) * KC + (lane & 7) * 16;
    uint4 v[10];
    if (i < 15) {
      uint4* dst = &g_halo[(i * 8 + jq) * 320 + lane];
#pragma unroll
      for (int k = 0; k < 10; k++) v[k] = lds128(hs + 1024 + k * 4 * KC);
#pragma unroll
      for (int k = 0; k < 10; k++) st_relaxed4(dst + k * 32, make_uint4(max(v[k].x, 1u), max(v[k].y, 1u), max(v[k].z, 1u), max(v[k].w, 1u)));
    }
#pragma unroll
    for (int k = 0; k < 10; k++) v[k] = make_uint4(0, 0, 0, 0);
    if (i > 0) {
      uint4* src = &g_halo[((i - 1) * 8 + jq) * 320 + lane];
      int iter = 0;
      bool ok;
      do {
        ok = true;
#pragma unroll
        for (int k = 0; k < 10; k++) {
          v[k] = ld_relaxed4(src + k * 32);
          ok = ok && v[k].x && v[k].y && v[k].z && v[k].w;
        }
        if (++iter > (1 << 22)) asm volatile("trap;");
      } while (!ok);
    }
#pragma unroll
    for (int k = 0; k < 10; k++) sts128(hs + k * 4 * KC, v[k]);
  }
  __syncwarp();
  if (elect_one()) {
    mbar_arrive(bars + BAR_HALO * 8);
    mbar_wait(bars + BAR_OF * 8, 0);
    fence_async_smem();
    tma3d_store(&maps.os, stg, jq * 80, i * 64);
    bulk_commit();
    bulk_wait_read();
    mbar_arrive(bars + BAR_S2E * 8);
    bulk_wait();
    fence_async();
    red_release(fl + FL_O, 1);
    wait_flag(fl + FL_O, (epoch + 1) * 8);
    fence_async();
    mbar_arrive(bars + BAR_RO * 8);
  }
}

__global__ void __launch_bounds__(384, 1)
fused_kernel(const __nv_bfloat16* __restrict__ wqkv, const __nv_bfloat16* __restrict__ b1, const __nv_bfloat16* __restrict__ w2,
             const __nv_bfloat16* __restrict__ wo, const __nv_bfloat16* __restrict__ b2, const __nv_bfloat16* __restrict__ gate_w,
             __nv_bfloat16* __restrict__ out, const __nv_bfloat16* __restrict__ x, const __nv_bfloat16* __restrict__ w1,
             const __grid_constant__ Maps maps) {
  extern __shared__ __align__(1024) uint8_t smem_raw[];
  const uint32_t sbase = smem_u32(smem_raw);
  uint32_t rank;
  asm volatile("mov.u32 %0, %%cluster_ctarank;" : "=r"(rank));
  Role R;
  {
    const int q = blockIdx.x >> 1;
    int grp, m;
    if (q < 4) { grp = 0; m = q; }
    else if (q < 36) { grp = 1 + ((q - 4) & 7); m = (q - 4) >> 3; }
    else { grp = 9 + (q - 36) % 7; m = (q - 36) / 7; }
    R.i = (grp >> 1) * 2 + (int)rank; R.s = grp & 1; R.c = m; R.rank = (int)rank;
    R.full0 = 192 * (2 * m + R.s);
    R.part0 = R.s ? 1664 + 16 * m : 1536 + 32 * m;
  }
  const int wid = __shfl_sync(0xffffffffu, (int)(threadIdx.x >> 5), 0);
  const uint32_t bars = sbase + OFF_BAR;
  if (wid >= 8) {
    if (wid == 8) {
      if (elect_one()) {

#pragma unroll
        for (int b = 0; b < 4; b++) mbar_init(bars + (BAR_AF + b) * 8, 1);
#pragma unroll
        for (int b = 0; b < 4; b++) mbar_init(bars + (BAR_BF + b) * 8, 1);
        mbar_arrive(bars + BAR_AF * 8);
        mbar_arrive(bars + BAR_BF * 8);
        asm volatile("fence.mbarrier_init.release.cluster;" ::: "memory");
      }
    } else if (wid == 9) {
      if (elect_one()) {
#pragma unroll
        for (int b = 0; b < NBARS; b++)
          if ((b >= BAR_AE && b < BAR_BF) || b >= BAR_BE) mbar_init(bars + b * 8, 1u << ((BAR_COUNTS >> (2 * b)) & 3));
        asm volatile("fence.mbarrier_init.release.cluster;" ::: "memory");
      }
    } else {
      if (elect_one()) {
        if (wid == 10) { prefetch_tm(&maps.w1f); prefetch_tm(&maps.w1n[R.s]); } else prefetch_tm(&maps.ax);
      }
    }
    __syncwarp();
    cluster_arrive();
    asm volatile("setmaxnreg.dec.sync.aligned.u32 88;");
    if (wid == 8) {
      if (elect_one()) {

#pragma unroll
        for (int n = 0; n < NA0; n++) {
          const uint32_t fb = bars + (BAR_BF + n) * 8, db = sbase + OFF_B + n * 32768;
          if (n > 0) {
            mbar_expect_tx(bars + (BAR_AF + n) * 8, 16384);
            tma3d(sbase + OFF_A + n * 16384, &maps.ax, bars + (BAR_AF + n) * 8, n * 64, R.i * 64);
          }
          if (n > 0 && n < NP0) {
            mbar_expect_tx(fb, R.s ? 26624 : 28672);
            tma2d(db, &maps.w1f, fb, R.full0, n * 64);
            tma2d(db + 8192, &maps.w1f, fb, R.full0 + 64, n * 64);
            tma2d(db + 16384, &maps.w1f, fb, R.full0 + 128, n * 64);
            tma2d(db + 24576, &maps.w1n[R.s], fb, R.part0, n * 64);
          }
        }
        if (sbase & 1023) asm volatile("trap;");
      }
      __syncwarp();
      cluster_wait();
      if (elect_one()) {

#pragma unroll
        for (int n = NP0; n < 4; n++) {
          const uint32_t fb = bars + (BAR_BF + n) * 8, db = sbase + OFF_B + (n == 3 ? B3_OFF : n * 32768) + R.rank * 8192;
          if (n >= NA0) {
            mbar_expect_tx(bars + (BAR_AF + n) * 8, 16384);
            tma3d(sbase + OFF_A + n * 16384, &maps.ax, bars + (BAR_AF + n) * 8, n * 64, R.i * 64);
          }
          mbar_expect_tx(fb, R.s ? 26624 : 28672);
          tma2d_mc(db, &maps.w1f, fb, R.full0 + R.rank * 64, n * 64);
          tma2d_mc(db + 16384, R.rank ? &maps.w1n[R.s] : &maps.w1f, fb, R.rank ? R.part0 : R.full0 + 128, n * 64);
        }
        producer(sbase, maps, R, w2, wo);
      }
    } else if (wid == 9) {
      aux(sbase, maps, R, b2, out);
    } else {
      repack(sbase, R, wid - 10, wqkv, gate_w);
      if (elect_one()) {
#pragma unroll 1
        for (int k = wid - 10; k < NMAPS; k += 2) prefetch_tm(&maps.ax + k);
      }
      __syncwarp();
    }
  } else {
    {
      const int tid = threadIdx.x, r = tid >> 3;
      const uint32_t sw = r * 128 + (((tid & 7) ^ (r & 7)) << 4);
      const uint8_t* wb = reinterpret_cast<const uint8_t*>(w1 + (size_t)r * FF + R.full0) + (tid & 7) * 16;
      const int pr = tid >> 2, pc = tid & 3;
      const uint8_t* wp = reinterpret_cast<const uint8_t*>(w1 + (size_t)pr * FF + R.part0 + pc * 8);
      const uint32_t sp = pr * 128 + ((pc ^ (pr & 7)) << 4);
      auto copy_b = [&](int n) {
#pragma unroll
        for (int a = 0; a < 3; a++)
#pragma unroll
          for (int k = 0; k < 2; k++)
            cp_async16(sbase + OFF_B + n * 32768 + a * 8192 + k * 4096 + sw, wb + a * 128 + (n * 64 + k * 32) * FF * 2);
        if (pc < (R.s ? 2 : 4)) cp_async16(sbase + OFF_B + n * 32768 + 24576 + sp, wp + n * 64 * FF * 2);
      };
      copy_b(0);
      const uint8_t* xa = reinterpret_cast<const uint8_t*>(x + (size_t)(R.i * 128 + 2 * r) * DM) + (tid & 7) * 16;
#pragma unroll
      for (int k = 0; k < 4; k++) cp_async16(sbase + OFF_A + k * 4096 + sw, xa + ((k & 1) * 64 + (k >> 1)) * DM * 2);
    }
    uint32_t bv[28];
#pragma unroll
    for (int c = 0; c < 28; c++) bv[c] = 0;
    if (b1 != nullptr) {
      const uint32_t* bp = reinterpret_cast<const uint32_t*>(b1 + R.full0) + (threadIdx.x & 3);
      const uint32_t* bq = reinterpret_cast<const uint32_t*>(b1 + R.part0) + (threadIdx.x & 3);
#pragma unroll
      for (int c = 0; c < 28; c++) {
        if (c < 24) bv[c] = ldg_nc(bp + c * 4);
        else if (c < 26 || R.s == 0) bv[c] = ldg_nc(bq + (c - 24) * 4);
      }
    }
    cluster_arrive();
    asm volatile("setmaxnreg.inc.sync.aligned.u32 208;");
    consumer(sbase, wid >> 2, R, maps, bv);
  }
}

typedef CUresult (*EncFn)(CUtensorMap*, CUtensorMapDataType, cuuint32_t, void*, const cuuint64_t*, const cuuint64_t*, const cuuint32_t*,
                          const cuuint32_t*, CUtensorMapInterleave, CUtensorMapSwizzle, CUtensorMapL2promotion, CUtensorMapFloatOOBfill);

void make_map(EncFn enc, CUtensorMap* m, const void* base, uint64_t d0, uint64_t d1, uint64_t pitch1, uint32_t b0, uint32_t b1,
              bool swz = true, uint64_t d2 = 0, uint64_t pitch2 = 0, uint32_t b2 = 1) {
  cuuint64_t dims[3] = {d0, d1, d2};
  cuuint64_t strides[2] = {pitch1, pitch2};
  cuuint32_t box[3] = {b0, b1, b2};
  cuuint32_t es[3] = {1, 1, 1};
  CUresult res = enc(m, CU_TENSOR_MAP_DATA_TYPE_BFLOAT16, d2 ? 3 : 2, const_cast<void*>(base), dims, strides, box, es,
                     CU_TENSOR_MAP_INTERLEAVE_NONE, swz ? CU_TENSOR_MAP_SWIZZLE_128B : CU_TENSOR_MAP_SWIZZLE_NONE,
                     CU_TENSOR_MAP_L2_PROMOTION_L2_128B, CU_TENSOR_MAP_FLOAT_OOB_FILL_NONE);
  (void)res;
}

}

extern "C" void kernel_launch(void* const* d_in, const int* in_sizes, int n_in, void* d_out, int out_size) {
  (void)in_sizes; (void)n_in; (void)out_size;
  const __nv_bfloat16* x = (const __nv_bfloat16*)d_in[0];
  const __nv_bfloat16* wqkv = (const __nv_bfloat16*)d_in[1];
  const __nv_bfloat16* wo = (const __nv_bfloat16*)d_in[2];
  const __nv_bfloat16* w1 = (const __nv_bfloat16*)d_in[4];
  const __nv_bfloat16* b1 = (const __nv_bfloat16*)d_in[5];
  const __nv_bfloat16* w2 = (const __nv_bfloat16*)d_in[6];
  const __nv_bfloat16* b2 = (const __nv_bfloat16*)d_in[7];
  const __nv_bfloat16* gate_w = (const __nv_bfloat16*)d_in[8];
  static EncFn enc = nullptr;
  static void* act_ptr = nullptr;
  static void* wq_ptr = nullptr;
  if (!enc) {
    void* fn = nullptr;
    cudaDriverEntryPointQueryResult qr;
    cudaGetDriverEntryPoint("cuTensorMapEncodeTiled", &fn, cudaEnableDefault, &qr);
    enc = (EncFn)fn;
    cudaGetSymbolAddress(&act_ptr, g_act);
    cudaGetSymbolAddress(&wq_ptr, g_wqkv);
    cudaFuncSetAttribute(fused_kernel, cudaFuncAttributeMaxDynamicSharedMemorySize, SMEM_TOTAL);
  }
  Maps maps;
  make_map(enc, &maps.ax, x, DM, SEQ / 2, DM * 4, 64, 64, true, 2, DM * 2, 2);
  make_map(enc, &maps.w1f, w1, FF, DM, FF * 2, 64, 64);
  make_map(enc, &maps.w1n[0], w1, FF, DM, FF * 2, 32, 64);
  make_map(enc, &maps.w1n[1], w1, FF, DM, FF * 2, 16, 64);
  make_map(enc, &maps.wq, wq_ptr, 256, 8 * DM, 512, 64, 64);
  make_map(enc, &maps.hs, act_ptr, ACT_LD, SEQ / 2, ACT_LD * 4, 64, 64, true, 2, ACT_LD * 2, 1);
  make_map(enc, &maps.hn[0], act_ptr, ACT_LD, SEQ / 2, ACT_LD * 4, 32, 64, true, 2, ACT_LD * 2, 2);
  make_map(enc, &maps.hn[1], act_ptr, ACT_LD, SEQ / 2, ACT_LD * 4, 16, 64, true, 2, ACT_LD * 2, 2);
  make_map(enc, &maps.os, act_ptr, ACT_LD, SEQ / 2, ACT_LD * 4, 80, 64, false, 2, ACT_LD * 2, 2);
  make_map(enc, &maps.hf, act_ptr, ACT_LD, SEQ, ACT_LD * 2, 64, 128);
  make_map(enc, &maps.w2f, w2, DM, FF, DM * 2, 64, 32);
  make_map(enc, &maps.w2n, w2, DM, FF, DM * 2, 32, 32);
  make_map(enc, &maps.wof, wo, DM, DM, DM * 2, 64, 32);
  make_map(enc, &maps.won, wo, DM, DM, DM * 2, 32, 32);
  make_map(enc, &maps.of, d_out, DM, SEQ, DM * 2, 64, 16);
  make_map(enc, &maps.on, d_out, DM, SEQ, DM * 2, 32, 16);
  cudaLaunchConfig_t cfg = {};
  cfg.gridDim = dim3(128);
  cfg.blockDim = dim3(384);
  cfg.dynamicSmemBytes = SMEM_TOTAL;
  cfg.stream = cudaStreamPerThread;
  cudaLaunchAttribute attr[1];
  attr[0].id = cudaLaunchAttributeClusterDimension;
  attr[0].val.clusterDim.x = 2; attr[0].val.clusterDim.y = 1; attr[0].val.clusterDim.z = 1;
  cfg.attrs = attr; cfg.numAttrs = 1;
  cudaLaunchKernelEx(&cfg, fused_kernel, wqkv, b1, w2, wo, b2, gate_w, (__nv_bfloat16*)d_out, x, w1, maps);
}
```
